```python
import torch

def _softmax(x, axis=-1):
    return torch.softmax(x, dim=axis)
def _gelu(x):
    return torch.nn.functional.gelu(x, approximate="tanh")
def _silu(x):
    return torch.nn.functional.silu(x)
def _sigmoid(x):
    return torch.sigmoid(x)
def _layernorm(x, axis=-1, eps=1e-5):
    m = x.mean(dim=axis, keepdim=True)
    v = x.var(dim=axis, keepdim=True, unbiased=False)
    return (x - m) / torch.sqrt(v + eps)
def _scatter_add(tgt, idx, src, axis=0):
    return tgt.clone().index_add_(axis, idx, src)
def _segment_sum(src, seg, n):
    out = torch.zeros((n,) + src.shape[1:], dtype=src.dtype)
    return out.index_add_(0, seg, src)
def _pad(x, pw):
    flat = tuple(v for pair in reversed(pw) for v in pair)
    return torch.nn.functional.pad(x, flat)

kernel_name = 'standalone__mha_softmax__near_ridge'

def setup_inputs():

    _w = (lambda a: (lambda t: t.to(torch.bfloat16) if t.is_floating_point() else t)(torch.as_tensor(a)))
    B, H, Sq, Sk, D = 16, 16, 512, 512, 256
    return {
        "q": _w((lambda *s: torch.randn(*s, dtype=torch.bfloat16) * 0.8)(B, H, Sq, D)),
        "k": _w((lambda *s: torch.randn(*s, dtype=torch.bfloat16) * 0.8)(B, H, Sk, D)),
        "v": _w((lambda *s: torch.randn(*s, dtype=torch.bfloat16) * 0.05)(B, H, Sk, D)),
    }

def reference(q, k, v):
    scale = q.shape[-1] ** -0.5
    scores = torch.einsum("bhqd,bhkd->bhqk", q, k) * scale
    p = _softmax(scores, axis=-1)
    return torch.einsum("bhqk,bhkd->bhqd", p, v)
```

```cpp
#include <cuda_runtime.h>
#include <cuda_bf16.h>
#include <cuda.h>
#include <stdint.h>

namespace {

constexpr int SEQ = 512;
constexpr int HD = 256;
constexpr int NHEADS = 256;
constexpr int NUNITS = NHEADS * 2;
constexpr int NTHREADS = 384;
#define PF_DIST 2
#define PF_KADD 1
#define PF_KV 1
#define PF_GAP 230
#define PF_INFLIGHT 8
#define PF_SUB 0
#define REPEAT 1
#define EXPMODE 4
#define PF_SKIP 0
#define PF_GRAN 128
#define PF_QUARTER 1
#define PF_QJ 1
#define PROMO CU_TENSOR_MAP_L2_PROMOTION_L2_128B
#define POLICY 5
#define HEADMASK 255
#define MAPPING 0
#define GATE 1
#define DBGI (blockIdx.x + ((EXPMODE == 4 && CL == 2) ? 120 : 0))
#define TR(i)

constexpr uint32_t SMEM_BASE = 1024;
constexpr uint32_t OFF_Q = 0;
constexpr uint32_t OFF_K = 65536;
constexpr uint32_t OFF_V = 131072;
constexpr uint32_t OFF_O = 196608;
constexpr uint32_t OFF_BAR = 229376;
constexpr uint32_t SMEM_BYTES = OFF_BAR + 256 + 512;
constexpr uint32_t BAR_QE = 16, BAR_KF = 32, BAR_KE = 64, BAR_VF = 96, BAR_VE = 128, BAR_QF = 160;
constexpr uint32_t DESC_Q = ((SMEM_BASE + OFF_Q) >> 4) | (1u << 16);
constexpr uint32_t DESC_K = ((SMEM_BASE + OFF_K) >> 4) | (1u << 16);
constexpr uint32_t DESC_V = ((SMEM_BASE + OFF_V) >> 4) | ((4096u >> 4) << 16);

struct TrueT { static constexpr bool value = true; };
struct FalseT { static constexpr bool value = false; };

template <int SCALE_D>
__device__ __forceinline__ void wgmma_qk(float (&d)[64], uint32_t loA, uint32_t loB) {
  asm volatile("{\n.reg .b64 da, db;\nmov.b64 da, {%64, 0x40000040};\nmov.b64 db, {%65, 0x40000040};\n"
    "wgmma.mma_async.sync.aligned.m64n128k16.f32.bf16.bf16 {%0, %1, %2, %3, %4, %5, %6, %7, %8, %9, %10, %11, %12, %13, %14, %15, %16, %17, %18, %19, %20, %21, %22, %23, %24, %25, %26, %27, %28, %29, %30, %31, %32, %33, %34, %35, %36, %37, %38, %39, %40, %41, %42, %43, %44, %45, %46, %47, %48, %49, %50, %51, %52, %53, %54, %55, %56, %57, %58, %59, %60, %61, %62, %63}, da, db, %66, 1, 1, 0, 0;\n}\n"
    : "+f"(d[0]), "+f"(d[1]), "+f"(d[2]), "+f"(d[3]), "+f"(d[4]), "+f"(d[5]), "+f"(d[6]), "+f"(d[7]), "+f"(d[8]), "+f"(d[9]), "+f"(d[10]), "+f"(d[11]), "+f"(d[12]), "+f"(d[13]), "+f"(d[14]), "+f"(d[15]), "+f"(d[16]), "+f"(d[17]), "+f"(d[18]), "+f"(d[19]), "+f"(d[20]), "+f"(d[21]), "+f"(d[22]), "+f"(d[23]), "+f"(d[24]), "+f"(d[25]), "+f"(d[26]), "+f"(d[27]), "+f"(d[28]), "+f"(d[29]), "+f"(d[30]), "+f"(d[31]), "+f"(d[32]), "+f"(d[33]), "+f"(d[34]), "+f"(d[35]), "+f"(d[36]), "+f"(d[37]), "+f"(d[38]), "+f"(d[39]), "+f"(d[40]), "+f"(d[41]), "+f"(d[42]), "+f"(d[43]), "+f"(d[44]), "+f"(d[45]), "+f"(d[46]), "+f"(d[47]), "+f"(d[48]), "+f"(d[49]), "+f"(d[50]), "+f"(d[51]), "+f"(d[52]), "+f"(d[53]), "+f"(d[54]), "+f"(d[55]), "+f"(d[56]), "+f"(d[57]), "+f"(d[58]), "+f"(d[59]), "+f"(d[60]), "+f"(d[61]), "+f"(d[62]), "+f"(d[63])
    : "r"(loA), "r"(loB), "n"(SCALE_D));
}
template <int SCALE_D>
__device__ __forceinline__ void wgmma_pv(float (&d)[128], uint32_t a0, uint32_t a1, uint32_t a2, uint32_t a3, uint32_t loB) {
  asm volatile("{\n.reg .b64 db;\nmov.b64 db, {%132, 0x40000040};\n"
    "wgmma.mma_async.sync.aligned.m64n256k16.f32.bf16.bf16 {%0, %1, %2, %3, %4, %5, %6, %7, %8, %9, %10, %11, %12, %13, %14, %15, %16, %17, %18, %19, %20, %21, %22, %23, %24, %25, %26, %27, %28, %29, %30, %31, %32, %33, %34, %35, %36, %37, %38, %39, %40, %41, %42, %43, %44, %45, %46, %47, %48, %49, %50, %51, %52, %53, %54, %55, %56, %57, %58, %59, %60, %61, %62, %63, %64, %65, %66, %67, %68, %69, %70, %71, %72, %73, %74, %75, %76, %77, %78, %79, %80, %81, %82, %83, %84, %85, %86, %87, %88, %89, %90, %91, %92, %93, %94, %95, %96, %97, %98, %99, %100, %101, %102, %103, %104, %105, %106, %107, %108, %109, %110, %111, %112, %113, %114, %115, %116, %117, %118, %119, %120, %121, %122, %123, %124, %125, %126, %127}, {%128, %129, %130, %131}, db, %133, 1, 1, 1;\n}\n"
    : "+f"(d[0]), "+f"(d[1]), "+f"(d[2]), "+f"(d[3]), "+f"(d[4]), "+f"(d[5]), "+f"(d[6]), "+f"(d[7]), "+f"(d[8]), "+f"(d[9]), "+f"(d[10]), "+f"(d[11]), "+f"(d[12]), "+f"(d[13]), "+f"(d[14]), "+f"(d[15]), "+f"(d[16]), "+f"(d[17]), "+f"(d[18]), "+f"(d[19]), "+f"(d[20]), "+f"(d[21]), "+f"(d[22]), "+f"(d[23]), "+f"(d[24]), "+f"(d[25]), "+f"(d[26]), "+f"(d[27]), "+f"(d[28]), "+f"(d[29]), "+f"(d[30]), "+f"(d[31]), "+f"(d[32]), "+f"(d[33]), "+f"(d[34]), "+f"(d[35]), "+f"(d[36]), "+f"(d[37]), "+f"(d[38]), "+f"(d[39]), "+f"(d[40]), "+f"(d[41]), "+f"(d[42]), "+f"(d[43]), "+f"(d[44]), "+f"(d[45]), "+f"(d[46]), "+f"(d[47]), "+f"(d[48]), "+f"(d[49]), "+f"(d[50]), "+f"(d[51]), "+f"(d[52]), "+f"(d[53]), "+f"(d[54]), "+f"(d[55]), "+f"(d[56]), "+f"(d[57]), "+f"(d[58]), "+f"(d[59]), "+f"(d[60]), "+f"(d[61]), "+f"(d[62]), "+f"(d[63]), "+f"(d[64]), "+f"(d[65]), "+f"(d[66]), "+f"(d[67]), "+f"(d[68]), "+f"(d[69]), "+f"(d[70]), "+f"(d[71]), "+f"(d[72]), "+f"(d[73]), "+f"(d[74]), "+f"(d[75]), "+f"(d[76]), "+f"(d[77]), "+f"(d[78]), "+f"(d[79]), "+f"(d[80]), "+f"(d[81]), "+f"(d[82]), "+f"(d[83]), "+f"(d[84]), "+f"(d[85]), "+f"(d[86]), "+f"(d[87]), "+f"(d[88]), "+f"(d[89]), "+f"(d[90]), "+f"(d[91]), "+f"(d[92]), "+f"(d[93]), "+f"(d[94]), "+f"(d[95]), "+f"(d[96]), "+f"(d[97]), "+f"(d[98]), "+f"(d[99]), "+f"(d[100]), "+f"(d[101]), "+f"(d[102]), "+f"(d[103]), "+f"(d[104]), "+f"(d[105]), "+f"(d[106]), "+f"(d[107]), "+f"(d[108]), "+f"(d[109]), "+f"(d[110]), "+f"(d[111]), "+f"(d[112]), "+f"(d[113]), "+f"(d[114]), "+f"(d[115]), "+f"(d[116]), "+f"(d[117]), "+f"(d[118]), "+f"(d[119]), "+f"(d[120]), "+f"(d[121]), "+f"(d[122]), "+f"(d[123]), "+f"(d[124]), "+f"(d[125]), "+f"(d[126]), "+f"(d[127])
    : "r"(a0), "r"(a1), "r"(a2), "r"(a3), "r"(loB), "n"(SCALE_D));
}

__device__ __forceinline__ void wg_fence() { asm volatile("wgmma.fence.sync.aligned;" ::: "memory"); }
__device__ __forceinline__ void wg_commit() { asm volatile("wgmma.commit_group.sync.aligned;" ::: "memory"); }
template <int N> __device__ __forceinline__ void wg_wait() { asm volatile("wgmma.wait_group.sync.aligned %0;" :: "n"(N) : "memory"); }

__device__ __forceinline__ void mbar_init(uint32_t a, int c) { asm volatile("mbarrier.init.shared::cta.b64 [%0], %1;" :: "r"(a), "r"(c) : "memory"); }
__device__ __forceinline__ void mbar_expect(uint32_t a, int b) { asm volatile("mbarrier.arrive.expect_tx.shared::cta.b64 _, [%0], %1;" :: "r"(a), "r"(b) : "memory"); }
__device__ __forceinline__ void mbar_arrive(uint32_t a) { asm volatile("mbarrier.arrive.shared::cta.b64 _, [%0];" :: "r"(a) : "memory"); }
__device__ __forceinline__ void mbar_arrive_cluster(uint32_t a) { asm volatile("mbarrier.arrive.shared::cluster.b64 _, [%0];" :: "r"(a) : "memory"); }
__device__ __forceinline__ void mbar_wait(uint32_t a, uint32_t ph) {
  asm volatile("{\n.reg .pred p;\n.reg .u32 cnt;\nmov.u32 cnt, 0;\n"
               "LAB_WAIT:\nmbarrier.try_wait.parity.shared::cta.b64 p, [%0], %1;\n@p bra LAB_DONE;\n"
               "add.u32 cnt, cnt, 1;\nsetp.lt.u32 p, cnt, 4194304;\n@p bra LAB_WAIT;\ntrap;\nLAB_DONE:\n}\n"
               :: "r"(a), "r"(ph) : "memory");
}
__device__ __forceinline__ void cluster_arrive() { asm volatile("barrier.cluster.arrive.relaxed.aligned;" ::: "memory"); }
__device__ __forceinline__ void cluster_wait() { asm volatile("barrier.cluster.wait.aligned;" ::: "memory"); }
__device__ __forceinline__ void bar_sync(int id, int n) { asm volatile("bar.sync %0, %1;" :: "r"(id), "r"(n) : "memory"); }
__device__ __forceinline__ void bar_arrive(int id, int n) { asm volatile("bar.arrive %0, %1;" :: "r"(id), "r"(n) : "memory"); }
__device__ __forceinline__ uint32_t mapa(uint32_t a, uint32_t cta) { uint32_t r; asm("mapa.shared::cluster.u32 %0, %1, %2;" : "=r"(r) : "r"(a), "r"(cta)); return r; }
__device__ __forceinline__ bool elect_one() {
  uint32_t p;
  asm volatile("{\n.reg .pred P;\nelect.sync _|P, 0xffffffff;\nselp.b32 %0, 1, 0, P;\n}\n" : "=r"(p));
  return p != 0;
}

__device__ __forceinline__ void tma_load_3d(uint32_t dst, const CUtensorMap* tm, int c0, int c1, int c2, uint32_t bar, uint64_t pol) {
  asm volatile("cp.async.bulk.tensor.3d.shared::cluster.global.mbarrier::complete_tx::bytes.L2::cache_hint [%0], [%1, {%3, %4, %5}], [%2], %6;"
               :: "r"(dst), "l"(tm), "r"(bar), "r"(c0), "r"(c1), "r"(c2), "l"(pol) : "memory");
}
__device__ __forceinline__ void tma_load_3d_mc(uint32_t dst, const CUtensorMap* tm, int c0, int c1, int c2, uint32_t bar, uint16_t mask, uint64_t pol) {
  asm volatile("cp.async.bulk.tensor.3d.shared::cluster.global.mbarrier::complete_tx::bytes.multicast::cluster.L2::cache_hint [%0], [%1, {%3, %4, %5}], [%2], %6, %7;"
               :: "r"(dst), "l"(tm), "r"(bar), "r"(c0), "r"(c1), "r"(c2), "h"(mask), "l"(pol) : "memory");
}
__device__ __forceinline__ void tma_store_3d(const CUtensorMap* tm, uint32_t src, int c0, int c1, int c2) {
  asm volatile("cp.async.bulk.tensor.3d.global.shared::cta.bulk_group [%0, {%2, %3, %4}], [%1];"
               :: "l"(tm), "r"(src), "r"(c0), "r"(c1), "r"(c2) : "memory");
}
#define PF_MODE 4
__device__ __forceinline__ void l2_prefetch_line(const char* p, uint32_t scratch) {
  asm volatile("cp.async.ca.shared.global.L2::128B [%0], [%1], 4;" :: "r"(scratch), "l"(p) : "memory");
}
template <int BYTES> __device__ __forceinline__ void l2_prefetch_warp0(const char* p, int lane) {
  #pragma unroll
  for (int i = 0; i < BYTES / (32 * 128); i++) asm volatile("prefetch.global.L2 [%0];" :: "l"(p + (i * 32 + lane) * 128) : "memory");
}
template <int BYTES> __device__ __forceinline__ void l2_prefetch_warp(const char* p, int lane, uint32_t scratch) {
  #pragma unroll
  for (int i = 0; i < BYTES / (32 * PF_GRAN); i++) l2_prefetch_line(p + (i * 32 + lane) * PF_GRAN, scratch);
}
__device__ __forceinline__ float ex2(float x) { float y; asm volatile("ex2.approx.ftz.f32 %0, %1;" : "=f"(y) : "f"(x)); return y; }
__device__ __forceinline__ void vadd(float& a, float b) { asm volatile("add.f32 %0, %0, %1;" : "+f"(a) : "f"(b)); }
__device__ __forceinline__ float rcp(float x) { float y; asm("rcp.approx.ftz.f32 %0, %1;" : "=f"(y) : "f"(x)); return y; }
__device__ __forceinline__ uint32_t pack_bf16(float lo, float hi) { uint32_t r; asm volatile("cvt.rn.bf16x2.f32 %0, %1, %2;" : "=r"(r) : "f"(hi), "f"(lo)); return r; }
__device__ __forceinline__ void stmatrix_x4(uint32_t a, uint32_t r0, uint32_t r1, uint32_t r2, uint32_t r3) {
  asm volatile("stmatrix.sync.aligned.m8n8.x4.shared.b16 [%0], {%1, %2, %3, %4};" :: "r"(a), "r"(r0), "r"(r1), "r"(r2), "r"(r3) : "memory");
}

template <int CL>
__global__ void __launch_bounds__(NTHREADS, 1)
mha_fwd_kernel(const __grid_constant__ CUtensorMap tmQ, const __grid_constant__ CUtensorMap tmK,
               const __grid_constant__ CUtensorMap tmV, const __grid_constant__ CUtensorMap tmO,
               const char* __restrict__ gQ, const char* __restrict__ gK, const char* __restrict__ gV,
               int unit0, int nunits, int nclusters) {
  extern __shared__ __align__(1024) char smem_raw[];
  const uint32_t sb = (uint32_t)__cvta_generic_to_shared(smem_raw);
  const uint32_t sBar = sb + OFF_BAR;
  const int tid = threadIdx.x;
  const int warp = __shfl_sync(0xffffffffu, tid >> 5, 0), lane = tid & 31;
  const uint32_t rank = blockIdx.x & (CL - 1);
  const int cluster_id = blockIdx.x / CL;
  if (CL == 4) asm volatile("griddepcontrol.launch_dependents;");
  if (cluster_id >= nclusters) return;
  const int ntiles = (nunits - cluster_id + nclusters - 1) / nclusters;
  auto qrow_of = [&](int t) { return ((unit0 + cluster_id + t * nclusters) * (128 * CL) + (int)rank * 128) & ((HEADMASK + 1) * SEQ - 1); };
  auto krow_of = [&](int t) { return qrow_of(t) & ~(SEQ - 1); };

  if (warp == 3) {
    l2_prefetch_warp0<32768>(gQ + (size_t)qrow_of(0) * (HD * 2), lane);
    l2_prefetch_warp0<65536 / CL>(gK + (size_t)krow_of(0) * (HD * 2) + rank * (65536 / CL), lane);
  }
  if (tid == 0) {
    if ((sb & 0xFFFFFF) != SMEM_BASE) __trap();
    asm volatile("st.shared.u32 [%0], %1;" :: "r"(sBar), "r"(0) : "memory");
    for (int i = 0; i < 2; i++) mbar_init(sBar + BAR_QE + 8 * i, 1);
    for (int i = 0; i < 8; i++) mbar_init(sBar + BAR_QF + 8 * i, 1);
    for (int i = 0; i < 4; i++) {
      mbar_init(sBar + BAR_KF + 8 * i, 1); mbar_init(sBar + BAR_KE + 8 * i, 2 * CL);
      mbar_init(sBar + BAR_VF + 8 * i, 1); mbar_init(sBar + BAR_VE + 8 * i, 2 * CL);
    }
    for (int i = 0; i < 4; i++) { mbar_expect(sBar + BAR_KF + 8 * i, 16384); mbar_expect(sBar + BAR_VF + 8 * i, 16384); }
    asm volatile("fence.mbarrier_init.release.cluster;" ::: "memory");
  }
  if (tid == 32) {
    asm volatile("prefetch.tensormap [%0];" :: "l"(&tmQ) : "memory");
    asm volatile("prefetch.tensormap [%0];" :: "l"(&tmK) : "memory");
    asm volatile("prefetch.tensormap [%0];" :: "l"(&tmV) : "memory");
    asm volatile("prefetch.tensormap [%0];" :: "l"(&tmO) : "memory");
  }
  cluster_arrive();
  cluster_wait();

  if (warp < 4) {
    asm volatile("setmaxnreg.dec.sync.aligned.u32 24;");
    uint64_t pol;
    if (POLICY == 1 || ((POLICY == 2 || POLICY == 4 || POLICY == 5) && warp == 2) || (POLICY == 5 && CL == 4)) asm volatile("createpolicy.fractional.L2::evict_first.b64 %0, 1.0;" : "=l"(pol));
    else if (POLICY == 3 || POLICY == 5 || (POLICY == 4 && warp != 2)) asm volatile("createpolicy.fractional.L2::evict_unchanged.b64 %0, 1.0;" : "=l"(pol));
    else asm volatile("createpolicy.fractional.L2::evict_normal.b64 %0, 1.0;" : "=l"(pol));
    if (warp == 0) {
      uint32_t ph = 1;
      for (int t = 0; t < ntiles; t++) {
        const int row0 = krow_of(t);
        #pragma unroll 1
        for (int j = 0; j < 4; j++) {
          #pragma unroll
          for (int i = 0; i < 4 / CL; i++) {
            const int c = i * CL + rank;
            mbar_wait(sBar + BAR_KE + 8 * c, ph);
            if (elect_one())
              tma_load_3d_mc(sb + OFF_K + c * 16384, &tmK, 0, row0 + j * 128, c, sBar + BAR_KF + 8 * c, (1 << CL) - 1, pol);
          }
          ph ^= 1;
        }
      }
    } else if (warp == 1) {
      uint32_t ph = 1;
      mbar_wait(sBar + BAR_QF + 24, 0);
      for (int t = 0; t < ntiles; t++) {
        const int row0 = krow_of(t);
        #pragma unroll 1
        for (int j = 0; j < 4; j++) {
          #pragma unroll
          for (int i = 0; i < 4 / CL; i++) {
            const int c = i * CL + rank;
            mbar_wait(sBar + BAR_VE + 8 * c, ph);
            if (elect_one()) {
              tma_load_3d_mc(sb + OFF_V + c * 16384, &tmV, 0, row0 + j * 128 + c * 32, 0, sBar + BAR_VF + 8 * c, (1 << CL) - 1, pol);
              if (i == 0) asm volatile("st.volatile.shared.u32 [%0], %1;" :: "r"(sBar), "r"(t * 4 + j + 1) : "memory");
            }
          }
          ph ^= 1;
        }
      }
    } else if (warp == 2) {
      uint32_t ph = 1;
      for (int t = 0; t < ntiles; t++) {
        const int row0 = qrow_of(t);
        #pragma unroll 1
        for (int w = 0; w < 2; w++) {
          mbar_wait(sBar + BAR_QE + 8 * w, ph);
          if (t == 0 && w == 1) mbar_wait(sBar + BAR_QF, 0);
          if (elect_one()) {
            #pragma unroll
            for (int c = 0; c < 4; c++) {
              mbar_expect(sBar + BAR_QF + 32 * w + 8 * c, 8192);
              tma_load_3d(sb + OFF_Q + w * 32768 + c * 8192, &tmQ, 0, row0 + w * 64, c, sBar + BAR_QF + 32 * w + 8 * c, pol);
            }
          }
        }
        ph ^= 1;
      }
    } else {
      const uint32_t scratch = sBar + 256 + lane * 16;
      const int sub = CL == 4 ? rank : ((unit0 + cluster_id) & 1) * 2 + rank;
      int prog = 0;
      #pragma unroll 1
      for (int t = 0; t < ntiles; t++) {
        const char* pq = gQ + (size_t)qrow_of(t) * (HD * 2) + lane * 128;
        const size_t kvoff = (size_t)krow_of(t) * (HD * 2) + sub * 16384 + lane * 128;
        #pragma unroll 1
        for (int pc = (t == 0 ? 24 : 0); pc < 48; pc++) {
          const char* ptr; int j = 0;
          if (pc < 8) ptr = pq + pc * 4096;
          else if (pc < 12) ptr = gK + kvoff + (pc - 8) * 4096;
          else if (pc < 20) ptr = pq + (pc - 4) * 4096;
          else if (pc < 24) ptr = gV + kvoff + (pc - 20) * 4096;
          else { j = (pc - 16) >> 3; ptr = ((pc & 4) ? gV : gK) + kvoff + j * 65536 + (pc & 3) * 4096; }
          const int need = t * 4 + j - PF_DIST;
          int it = 0;
          while (prog <= need || prog == 0) {
            asm volatile("ld.volatile.shared.u32 %0, [%1];" : "=r"(prog) : "r"(sBar) : "memory");
            if (prog > need && prog > 0) break;
            __nanosleep(100);
            if (++it > (1 << 24)) __trap();
          }
          asm volatile("cp.async.wait_group %0;" :: "n"(PF_INFLIGHT - 1) : "memory");
          l2_prefetch_line(ptr, scratch);
          asm volatile("cp.async.commit_group;" ::: "memory");
        }
      }
      asm volatile("cp.async.wait_all;" ::: "memory");
    }
    cluster_arrive();
    cluster_wait();
  } else {
    asm volatile("setmaxnreg.inc.sync.aligned.u32 240;");
    const int w = (warp >> 2) - 1;
    const int wi = warp & 3;
    const int tid_in_wg = tid & 127;
    constexpr float cs = 0.0625f * 1.4426950408889634f;
    constexpr float TAU_RAW = 8.0f / cs;
    const uint32_t remBar = mapa(sBar, wi & (CL - 1)) + 8 * wi;
    const bool armer = (w == 0) && (wi == 3) && (lane == 0);
    const uint32_t descQ = DESC_Q + w * (32768 >> 4);
    const uint32_t sO = sb + OFF_O + (w * 4 + wi) * 4096;
    const uint32_t sO_lane = sO + ((lane & 7) + ((lane >> 3) & 1) * 8) * 128;
    const uint32_t sxor = ((lane >> 4) ^ (lane & 7)) << 4;

    float o[128];
    float s[64];
    uint32_t p[32];
    uint32_t kvph = 0, qph = 0;
    float m0 = 0.f, m1 = 0.f, l0 = 0.f, l1 = 0.f;
    int th0 = 0, th1 = 0;
    int orow_prev = 0;
    if (w == 1) bar_arrive(1, 256);

    auto pack_half = [&](uint32_t (&r)[32], int h) {
      #pragma unroll
      for (int i = 0; i < 16; i++) {
        r[2 * i] = pack_bf16(o[64 * h + 4 * i] * l0, o[64 * h + 4 * i + 1] * l0);
        r[2 * i + 1] = pack_bf16(o[64 * h + 4 * i + 2] * l1, o[64 * h + 4 * i + 3] * l1);
      }
    };
    auto store_half = [&](const uint32_t (&r)[32], int orow, int h) {
      if (lane == 0) asm volatile("cp.async.bulk.wait_group.read 0;" ::: "memory");
      __syncwarp();
      #pragma unroll
      for (int q = 0; q < 8; q++)
        stmatrix_x4(sO_lane + (q >> 2) * 2048 + (sxor ^ (((q * 2) & 7) << 4)), r[4 * q], r[4 * q + 1], r[4 * q + 2], r[4 * q + 3]);
      asm volatile("fence.proxy.async.shared::cta;" ::: "memory");
      __syncwarp();
      if (lane == 0) {
        tma_store_3d(&tmO, sO, 0, orow, h * 2);
        asm volatile("cp.async.bulk.commit_group;" ::: "memory");
      }
    };

    auto block = [&](auto first_tag, int t, int j) {
      constexpr bool FIRST = decltype(first_tag)::value;
      uint32_t ob[32];
      #pragma unroll
      for (int i = 0; i < 64; i++) asm volatile("" : "=f"(s[i]));
      TR(0);
      bar_sync(1 + w, 256);
      TR(1);
      #pragma unroll
      for (int c = 0; c < 4; c++) {
        if (FIRST) mbar_wait(sBar + BAR_QF + 32 * w + 8 * c, qph);
        mbar_wait(sBar + BAR_KF + 8 * c, kvph);
        if (armer) mbar_expect(sBar + BAR_KF + 8 * c, 16384);
        if (c == 0) TR(2);
        wg_fence();
        if (c == 0) wgmma_qk<0>(s, descQ, DESC_K);
        else wgmma_qk<1>(s, descQ + ((c * 8192) >> 4), DESC_K + ((c * 16384) >> 4));
        #pragma unroll
        for (int kk = 1; kk < 4; kk++)
          wgmma_qk<1>(s, descQ + ((c * 8192 + kk * 32) >> 4), DESC_K + ((c * 16384 + kk * 32) >> 4));
        wg_commit();
        if (FIRST && c == 1) { wg_wait<2>(); pack_half(ob, 1); }
      }
      bar_arrive(2 - w, 256);
      if (FIRST && t > 0) store_half(ob, orow_prev, 1);
      TR(3);
      wg_wait<3>(); if (tid_in_wg == 0) mbar_arrive_cluster(remBar + BAR_KE);
      wg_wait<2>(); if (tid_in_wg == 32) mbar_arrive_cluster(remBar + BAR_KE);
      wg_wait<1>(); if (tid_in_wg == 64) mbar_arrive_cluster(remBar + BAR_KE);
      wg_wait<0>(); if (tid_in_wg == 96) mbar_arrive_cluster(remBar + BAR_KE);
      if (!FIRST && j == 3 && wi == 2 && lane == 0) mbar_arrive(sBar + BAR_QE + 8 * w);
      TR(4);

      bool refresh = FIRST;
      if (!FIRST) {
        int a0 = __vimax3_s32(__float_as_int(s[0]), __float_as_int(s[1]), __float_as_int(s[4]));
        int a1 = __vimax3_s32(__float_as_int(s[2]), __float_as_int(s[3]), __float_as_int(s[6]));
        int b0 = __vimax3_s32(__float_as_int(s[5]), __float_as_int(s[8]), __float_as_int(s[9]));
        int b1 = __vimax3_s32(__float_as_int(s[7]), __float_as_int(s[10]), __float_as_int(s[11]));
        #pragma unroll
        for (int i = 3; i < 15; i += 2) {
          a0 = __vimax3_s32(a0, __float_as_int(s[4 * i]), __float_as_int(s[4 * i + 1]));
          a1 = __vimax3_s32(a1, __float_as_int(s[4 * i + 2]), __float_as_int(s[4 * i + 3]));
          b0 = __vimax3_s32(b0, __float_as_int(s[4 * i + 4]), __float_as_int(s[4 * i + 5]));
          b1 = __vimax3_s32(b1, __float_as_int(s[4 * i + 6]), __float_as_int(s[4 * i + 7]));
        }
        a0 = __vimax3_s32(a0, __float_as_int(s[60]), __float_as_int(s[61]));
        a1 = __vimax3_s32(a1, __float_as_int(s[62]), __float_as_int(s[63]));
        refresh = __any_sync(0xffffffffu, (max(a0, b0) >= th0) || (max(a1, b1) >= th1));
      }
      if (refresh) {
        float x0 = fmaxf(s[0], s[1]), x1 = fmaxf(s[2], s[3]), y0 = fmaxf(s[4], s[5]), y1 = fmaxf(s[6], s[7]);
        #pragma unroll
        for (int i = 2; i < 16; i += 2) {
          x0 = fmaxf(x0, fmaxf(s[4 * i], s[4 * i + 1]));
          x1 = fmaxf(x1, fmaxf(s[4 * i + 2], s[4 * i + 3]));
          y0 = fmaxf(y0, fmaxf(s[4 * i + 4], s[4 * i + 5]));
          y1 = fmaxf(y1, fmaxf(s[4 * i + 6], s[4 * i + 7]));
        }
        x0 = fmaxf(x0, y0); x1 = fmaxf(x1, y1);
        x0 = fmaxf(x0, __shfl_xor_sync(0xffffffffu, x0, 1));
        x1 = fmaxf(x1, __shfl_xor_sync(0xffffffffu, x1, 1));
        x0 = fmaxf(x0, __shfl_xor_sync(0xffffffffu, x0, 2));
        x1 = fmaxf(x1, __shfl_xor_sync(0xffffffffu, x1, 2));
        if (FIRST) {
          l0 = 0.f; l1 = 0.f;
        } else {
          x0 = fmaxf(x0, m0); x1 = fmaxf(x1, m1);
          const float a0 = ex2((m0 - x0) * cs), a1 = ex2((m1 - x1) * cs);
          l0 *= a0; l1 *= a1;
          #pragma unroll
          for (int i = 0; i < 32; i++) {
            o[4 * i] *= a0; o[4 * i + 1] *= a0; o[4 * i + 2] *= a1; o[4 * i + 3] *= a1;
          }
        }
        m0 = x0; m1 = x1;
        const float t0 = x0 + TAU_RAW, t1 = x1 + TAU_RAW;
        th0 = t0 > 0.f ? __float_as_int(t0) : (int)0x80000000;
        th1 = t1 > 0.f ? __float_as_int(t1) : (int)0x80000000;
      }
      const float mc0 = -m0 * cs, mc1 = -m1 * cs;
      if (FIRST) {
        #pragma unroll
        for (int i = 0; i < 128; i++) asm volatile("" : "=f"(o[i]));
      }

      #pragma unroll
      for (int c = 0; c < 4; c++) {
        #pragma unroll
        for (int i = 4 * c; i < 4 * c + 4; i++) {
          const float e0 = ex2(fmaf(s[4 * i], cs, mc0)), e1 = ex2(fmaf(s[4 * i + 1], cs, mc0));
          const float e2 = ex2(fmaf(s[4 * i + 2], cs, mc1)), e3 = ex2(fmaf(s[4 * i + 3], cs, mc1));
          vadd(l0, e0); vadd(l1, e2); vadd(l0, e1); vadd(l1, e3);
          p[2 * i] = pack_bf16(e0, e1);
          p[2 * i + 1] = pack_bf16(e2, e3);
        }
        if (c == 0) continue;
        if (c == 1) { TR(5); bar_sync(1 + w + (p[15] >> 31), 256); TR(6); }
        #pragma unroll
        for (int cc = (c == 1 ? 0 : c); cc <= c; cc++) {
          mbar_wait(sBar + BAR_VF + 8 * cc, kvph);
          if (armer) mbar_expect(sBar + BAR_VF + 8 * cc, 16384);
          if (cc == 0) TR(7);
          wg_fence();
          if (FIRST && cc == 0) wgmma_pv<0>(o, p[0], p[1], p[2], p[3], DESC_V);
          else wgmma_pv<1>(o, p[8 * cc], p[8 * cc + 1], p[8 * cc + 2], p[8 * cc + 3], DESC_V + ((cc * 16384) >> 4));
          wgmma_pv<1>(o, p[8 * cc + 4], p[8 * cc + 5], p[8 * cc + 6], p[8 * cc + 7], DESC_V + ((cc * 16384 + 2048) >> 4));
          wg_commit();
        }
      }
      if (FIRST || !(w == 1 && j == 3 && t == ntiles - 1)) bar_arrive(2 - w, 256);
      if (!FIRST && j == 3) {
        l0 += __shfl_xor_sync(0xffffffffu, l0, 1);
        l1 += __shfl_xor_sync(0xffffffffu, l1, 1);
        l0 += __shfl_xor_sync(0xffffffffu, l0, 2);
        l1 += __shfl_xor_sync(0xffffffffu, l1, 2);
        l0 = rcp(l0); l1 = rcp(l1);
      }
      TR(8);
      wg_wait<3>(); if (tid_in_wg == 0) mbar_arrive_cluster(remBar + BAR_VE);
      wg_wait<2>(); if (tid_in_wg == 32) mbar_arrive_cluster(remBar + BAR_VE);
      wg_wait<1>(); if (tid_in_wg == 64) mbar_arrive_cluster(remBar + BAR_VE);
      wg_wait<0>(); if (tid_in_wg == 96) mbar_arrive_cluster(remBar + BAR_VE);
      kvph ^= 1;
      TR(9);
    };

    #pragma unroll
    for (int i = 64; i < 128; i++) o[i] = 0.f;
    for (int t = 0; t < ntiles; t++) {
      block(TrueT{}, t, 0);
      #pragma unroll 1
      for (int j = 1; j < 4; j++) block(FalseT{}, t, j);
      qph ^= 1;
      orow_prev = (unit0 + cluster_id + t * nclusters) * (128 * CL) + rank * 128 + w * 64 + wi * 16;
      uint32_t oa[32];
      pack_half(oa, 0);
      store_half(oa, orow_prev, 0);
    }
    {
      uint32_t ob[32];
      pack_half(ob, 1);
      store_half(ob, orow_prev, 1);
    }
    if (lane == 0) asm volatile("cp.async.bulk.wait_group.read 0;" ::: "memory");
    __syncwarp();
    cluster_arrive();
    cluster_wait();
  }
}

typedef CUresult (*EncodeFn)(CUtensorMap*, CUtensorMapDataType, cuuint32_t, void*, const cuuint64_t*, const cuuint64_t*,
                             const cuuint32_t*, const cuuint32_t*, CUtensorMapInterleave, CUtensorMapSwizzle,
                             CUtensorMapL2promotion, CUtensorMapFloatOOBfill);

void make_map(EncodeFn enc, CUtensorMap* tm, void* ptr, uint32_t rows, uint32_t chunks) {
  cuuint64_t dims[3] = {64, (cuuint64_t)NHEADS * SEQ, 4};
  cuuint64_t strides[2] = {HD * 2, 128};
  cuuint32_t box[3] = {64, rows, chunks};
  cuuint32_t es[3] = {1, 1, 1};
  enc(tm, CU_TENSOR_MAP_DATA_TYPE_BFLOAT16, 3, ptr, dims, strides, box, es, CU_TENSOR_MAP_INTERLEAVE_NONE,
      CU_TENSOR_MAP_SWIZZLE_128B, PROMO, CU_TENSOR_MAP_FLOAT_OOB_FILL_NONE);
}

}

extern "C" void kernel_launch(void* const* d_in, const int* in_sizes, int n_in, void* d_out, int out_size) {
  static EncodeFn enc = nullptr;
  static int nblocks = 0;
  if (!enc) {
    void* fn = nullptr;
    cudaDriverEntryPointQueryResult st;
    cudaGetDriverEntryPoint("cuTensorMapEncodeTiled", &fn, cudaEnableDefault, &st);
    enc = (EncodeFn)fn;
    cudaFuncSetAttribute(mha_fwd_kernel<2>, cudaFuncAttributeMaxDynamicSharedMemorySize, SMEM_BYTES);
    cudaFuncSetAttribute(mha_fwd_kernel<4>, cudaFuncAttributeMaxDynamicSharedMemorySize, SMEM_BYTES);
    int dev = 0, sms = 0;
    cudaGetDevice(&dev);
    cudaDeviceGetAttribute(&sms, cudaDevAttrMultiProcessorCount, dev);
    nblocks = sms & ~1;
  }
  CUtensorMap tmQ, tmK, tmV, tmO;
  make_map(enc, &tmQ, d_in[0], 64, 1);
  make_map(enc, &tmK, d_in[1], 128, 1);
  make_map(enc, &tmV, d_in[2], 32, 4);
  make_map(enc, &tmO, d_out, 16, 2);
  cudaLaunchConfig_t cfg = {};
  cfg.blockDim = dim3(NTHREADS); cfg.dynamicSmemBytes = SMEM_BYTES; cfg.stream = cudaStreamPerThread;
  cudaLaunchAttribute at[1];
  at[0].id = cudaLaunchAttributeClusterDimension; at[0].val.clusterDim.y = 1; at[0].val.clusterDim.z = 1;
  cfg.attrs = at; cfg.numAttrs = 1;
  const char *q = (const char*)d_in[0], *k = (const char*)d_in[1], *v = (const char*)d_in[2];
  {
    static int nA = -1;
    if (nA < 0) {
      at[0].val.clusterDim.x = 4; cfg.gridDim = dim3(128);
      cudaOccupancyMaxActiveClusters(&nA, mha_fwd_kernel<4>, &cfg);
      if (nA > 32) nA = 32;
    }
    const int nB = (nblocks - 4 * nA) / 2;
    const int hA = nB > 0 ? (8 * nA < NHEADS ? 8 * nA : NHEADS) : NHEADS;
    at[0].val.clusterDim.x = 4; cfg.gridDim = dim3(4 * nA);
    cudaLaunchKernelEx(&cfg, mha_fwd_kernel<4>, tmQ, tmK, tmV, tmO, q, k, v, 0, hA, nA);
    if (hA < NHEADS) {
      cudaLaunchAttribute at2[2];
      at2[0] = at[0]; at2[0].val.clusterDim.x = 2;
      at2[1].id = cudaLaunchAttributeProgrammaticStreamSerialization; at2[1].val.programmaticStreamSerializationAllowed = 1;
      cfg.attrs = at2; cfg.numAttrs = 2; cfg.gridDim = dim3(2 * nB);
      cudaLaunchKernelEx(&cfg, mha_fwd_kernel<2>, tmQ, tmK, tmV, tmO, q, k, v, 2 * hA, 2 * (NHEADS - hA), nB);
    }
  }
}
```

```cpp
#include <cuda_runtime.h>
#include <cuda_bf16.h>
#include <cuda.h>
#include <stdint.h>

namespace {

constexpr int SEQ = 512;
constexpr int HD = 256;
constexpr int NHEADS = 256;
constexpr int NTHREADS = 384;
#define PF_DIST 2
#define PF_INFLIGHT 2
#define DYNAMIC 1

constexpr uint32_t SMEM_BASE = 1024;
constexpr uint32_t OFF_Q = 0;
constexpr uint32_t OFF_K = 65536;
constexpr uint32_t OFF_V = 131072;
constexpr uint32_t OFF_O = 196608;
constexpr uint32_t OFF_BAR = 229376;
constexpr uint32_t SMEM_BYTES = OFF_BAR + 512 + 2048;
constexpr uint32_t W_PROG = 0, W_DYN = 4, BAR_DYN = 8, BAR_QE = 16, BAR_KF = 32, BAR_KE = 64, BAR_VF = 96, BAR_VE = 128,
                   BAR_QF = 160  , BAR_PF = 256, OFF_PFDST = 512;
constexpr uint32_t DESC_Q = ((SMEM_BASE + OFF_Q) >> 4) | (1u << 16);
constexpr uint32_t DESC_K = ((SMEM_BASE + OFF_K) >> 4) | (1u << 16);
constexpr uint32_t DESC_V = ((SMEM_BASE + OFF_V) >> 4) | ((4096u >> 4) << 16);

__device__ unsigned int g_ticket;

struct TrueT { static constexpr bool value = true; };
struct FalseT { static constexpr bool value = false; };

template <int SCALE_D>
__device__ __forceinline__ void wgmma_qk(float (&d)[64], uint32_t loA, uint32_t loB) {
  asm volatile("{\n.reg .b64 da, db;\nmov.b64 da, {%64, 0x40000040};\nmov.b64 db, {%65, 0x40000040};\n"
    "wgmma.mma_async.sync.aligned.m64n128k16.f32.bf16.bf16 {%0, %1, %2, %3, %4, %5, %6, %7, %8, %9, %10, %11, %12, %13, %14, %15, %16, %17, %18, %19, %20, %21, %22, %23, %24, %25, %26, %27, %28, %29, %30, %31, %32, %33, %34, %35, %36, %37, %38, %39, %40, %41, %42, %43, %44, %45, %46, %47, %48, %49, %50, %51, %52, %53, %54, %55, %56, %57, %58, %59, %60, %61, %62, %63}, da, db, %66, 1, 1, 0, 0;\n}\n"
    : "+f"(d[0]), "+f"(d[1]), "+f"(d[2]), "+f"(d[3]), "+f"(d[4]), "+f"(d[5]), "+f"(d[6]), "+f"(d[7]), "+f"(d[8]), "+f"(d[9]), "+f"(d[10]), "+f"(d[11]), "+f"(d[12]), "+f"(d[13]), "+f"(d[14]), "+f"(d[15]), "+f"(d[16]), "+f"(d[17]), "+f"(d[18]), "+f"(d[19]), "+f"(d[20]), "+f"(d[21]), "+f"(d[22]), "+f"(d[23]), "+f"(d[24]), "+f"(d[25]), "+f"(d[26]), "+f"(d[27]), "+f"(d[28]), "+f"(d[29]), "+f"(d[30]), "+f"(d[31]), "+f"(d[32]), "+f"(d[33]), "+f"(d[34]), "+f"(d[35]), "+f"(d[36]), "+f"(d[37]), "+f"(d[38]), "+f"(d[39]), "+f"(d[40]), "+f"(d[41]), "+f"(d[42]), "+f"(d[43]), "+f"(d[44]), "+f"(d[45]), "+f"(d[46]), "+f"(d[47]), "+f"(d[48]), "+f"(d[49]), "+f"(d[50]), "+f"(d[51]), "+f"(d[52]), "+f"(d[53]), "+f"(d[54]), "+f"(d[55]), "+f"(d[56]), "+f"(d[57]), "+f"(d[58]), "+f"(d[59]), "+f"(d[60]), "+f"(d[61]), "+f"(d[62]), "+f"(d[63])
    : "r"(loA), "r"(loB), "n"(SCALE_D));
}
template <int SCALE_D>
__device__ __forceinline__ void wgmma_pv(float (&d)[128], uint32_t a0, uint32_t a1, uint32_t a2, uint32_t a3, uint32_t loB) {
  asm volatile("{\n.reg .b64 db;\nmov.b64 db, {%132, 0x40000040};\n"
    "wgmma.mma_async.sync.aligned.m64n256k16.f32.bf16.bf16 {%0, %1, %2, %3, %4, %5, %6, %7, %8, %9, %10, %11, %12, %13, %14, %15, %16, %17, %18, %19, %20, %21, %22, %23, %24, %25, %26, %27, %28, %29, %30, %31, %32, %33, %34, %35, %36, %37, %38, %39, %40, %41, %42, %43, %44, %45, %46, %47, %48, %49, %50, %51, %52, %53, %54, %55, %56, %57, %58, %59, %60, %61, %62, %63, %64, %65, %66, %67, %68, %69, %70, %71, %72, %73, %74, %75, %76, %77, %78, %79, %80, %81, %82, %83, %84, %85, %86, %87, %88, %89, %90, %91, %92, %93, %94, %95, %96, %97, %98, %99, %100, %101, %102, %103, %104, %105, %106, %107, %108, %109, %110, %111, %112, %113, %114, %115, %116, %117, %118, %119, %120, %121, %122, %123, %124, %125, %126, %127}, {%128, %129, %130, %131}, db, %133, 1, 1, 1;\n}\n"
    : "+f"(d[0]), "+f"(d[1]), "+f"(d[2]), "+f"(d[3]), "+f"(d[4]), "+f"(d[5]), "+f"(d[6]), "+f"(d[7]), "+f"(d[8]), "+f"(d[9]), "+f"(d[10]), "+f"(d[11]), "+f"(d[12]), "+f"(d[13]), "+f"(d[14]), "+f"(d[15]), "+f"(d[16]), "+f"(d[17]), "+f"(d[18]), "+f"(d[19]), "+f"(d[20]), "+f"(d[21]), "+f"(d[22]), "+f"(d[23]), "+f"(d[24]), "+f"(d[25]), "+f"(d[26]), "+f"(d[27]), "+f"(d[28]), "+f"(d[29]), "+f"(d[30]), "+f"(d[31]), "+f"(d[32]), "+f"(d[33]), "+f"(d[34]), "+f"(d[35]), "+f"(d[36]), "+f"(d[37]), "+f"(d[38]), "+f"(d[39]), "+f"(d[40]), "+f"(d[41]), "+f"(d[42]), "+f"(d[43]), "+f"(d[44]), "+f"(d[45]), "+f"(d[46]), "+f"(d[47]), "+f"(d[48]), "+f"(d[49]), "+f"(d[50]), "+f"(d[51]), "+f"(d[52]), "+f"(d[53]), "+f"(d[54]), "+f"(d[55]), "+f"(d[56]), "+f"(d[57]), "+f"(d[58]), "+f"(d[59]), "+f"(d[60]), "+f"(d[61]), "+f"(d[62]), "+f"(d[63]), "+f"(d[64]), "+f"(d[65]), "+f"(d[66]), "+f"(d[67]), "+f"(d[68]), "+f"(d[69]), "+f"(d[70]), "+f"(d[71]), "+f"(d[72]), "+f"(d[73]), "+f"(d[74]), "+f"(d[75]), "+f"(d[76]), "+f"(d[77]), "+f"(d[78]), "+f"(d[79]), "+f"(d[80]), "+f"(d[81]), "+f"(d[82]), "+f"(d[83]), "+f"(d[84]), "+f"(d[85]), "+f"(d[86]), "+f"(d[87]), "+f"(d[88]), "+f"(d[89]), "+f"(d[90]), "+f"(d[91]), "+f"(d[92]), "+f"(d[93]), "+f"(d[94]), "+f"(d[95]), "+f"(d[96]), "+f"(d[97]), "+f"(d[98]), "+f"(d[99]), "+f"(d[100]), "+f"(d[101]), "+f"(d[102]), "+f"(d[103]), "+f"(d[104]), "+f"(d[105]), "+f"(d[106]), "+f"(d[107]), "+f"(d[108]), "+f"(d[109]), "+f"(d[110]), "+f"(d[111]), "+f"(d[112]), "+f"(d[113]), "+f"(d[114]), "+f"(d[115]), "+f"(d[116]), "+f"(d[117]), "+f"(d[118]), "+f"(d[119]), "+f"(d[120]), "+f"(d[121]), "+f"(d[122]), "+f"(d[123]), "+f"(d[124]), "+f"(d[125]), "+f"(d[126]), "+f"(d[127])
    : "r"(a0), "r"(a1), "r"(a2), "r"(a3), "r"(loB), "n"(SCALE_D));
}

__device__ __forceinline__ void wg_fence() { asm volatile("wgmma.fence.sync.aligned;" ::: "memory"); }
__device__ __forceinline__ void wg_commit() { asm volatile("wgmma.commit_group.sync.aligned;" ::: "memory"); }
template <int N> __device__ __forceinline__ void wg_wait() { asm volatile("wgmma.wait_group.sync.aligned %0;" :: "n"(N) : "memory"); }

__device__ __forceinline__ void mbar_init(uint32_t a, int c) { asm volatile("mbarrier.init.shared::cta.b64 [%0], %1;" :: "r"(a), "r"(c) : "memory"); }
__device__ __forceinline__ void mbar_expect(uint32_t a, int b) { asm volatile("mbarrier.arrive.expect_tx.shared::cta.b64 _, [%0], %1;" :: "r"(a), "r"(b) : "memory"); }
__device__ __forceinline__ void mbar_arrive(uint32_t a) { asm volatile("mbarrier.arrive.shared::cta.b64 _, [%0];" :: "r"(a) : "memory"); }
__device__ __forceinline__ void mbar_arrive_cluster(uint32_t a) { asm volatile("mbarrier.arrive.shared::cluster.b64 _, [%0];" :: "r"(a) : "memory"); }
__device__ __forceinline__ void mbar_wait(uint32_t a, uint32_t ph) {
  asm volatile("{\n.reg .pred p;\n.reg .u32 cnt;\nmov.u32 cnt, 0;\n"
               "LAB_WAIT:\nmbarrier.try_wait.parity.shared::cta.b64 p, [%0], %1;\n@p bra LAB_DONE;\n"
               "add.u32 cnt, cnt, 1;\nsetp.lt.u32 p, cnt, 4194304;\n@p bra LAB_WAIT;\ntrap;\nLAB_DONE:\n}\n"
               :: "r"(a), "r"(ph) : "memory");
}
__device__ __forceinline__ void cluster_arrive() { asm volatile("barrier.cluster.arrive.relaxed.aligned;" ::: "memory"); }
__device__ __forceinline__ void cluster_wait() { asm volatile("barrier.cluster.wait.aligned;" ::: "memory"); }
__device__ __forceinline__ void bar_sync(int id, int n) { asm volatile("bar.sync %0, %1;" :: "r"(id), "r"(n) : "memory"); }
__device__ __forceinline__ void bar_arrive(int id, int n) { asm volatile("bar.arrive %0, %1;" :: "r"(id), "r"(n) : "memory"); }
__device__ __forceinline__ uint32_t mapa(uint32_t a, uint32_t cta) { uint32_t r; asm("mapa.shared::cluster.u32 %0, %1, %2;" : "=r"(r) : "r"(a), "r"(cta)); return r; }
__device__ __forceinline__ int lds_volatile(uint32_t a) { int v; asm volatile("ld.volatile.shared.u32 %0, [%1];" : "=r"(v) : "r"(a) : "memory"); return v; }
__device__ __forceinline__ bool elect_one() {
  uint32_t p;
  asm volatile("{\n.reg .pred P;\nelect.sync _|P, 0xffffffff;\nselp.b32 %0, 1, 0, P;\n}\n" : "=r"(p));
  return p != 0;
}

__device__ __forceinline__ void tma_load_3d(uint32_t dst, const CUtensorMap* tm, int c1, int c2, uint32_t bar, uint64_t pol) {
  asm volatile("cp.async.bulk.tensor.3d.shared::cluster.global.mbarrier::complete_tx::bytes.L2::cache_hint [%0], [%1, {%3, %4, %5}], [%2], %6;"
               :: "r"(dst), "l"(tm), "r"(bar), "r"(0), "r"(c1), "r"(c2), "l"(pol) : "memory");
}
__device__ __forceinline__ void tma_load_3d_mc(uint32_t dst, const CUtensorMap* tm, int c1, int c2, uint32_t bar, uint16_t mask, uint64_t pol) {
  asm volatile("cp.async.bulk.tensor.3d.shared::cluster.global.mbarrier::complete_tx::bytes.multicast::cluster.L2::cache_hint [%0], [%1, {%3, %4, %5}], [%2], %6, %7;"
               :: "r"(dst), "l"(tm), "r"(bar), "r"(0), "r"(c1), "r"(c2), "h"(mask), "l"(pol) : "memory");
}
__device__ __forceinline__ void tma_store_3d(const CUtensorMap* tm, uint32_t src, int c1) {
  asm volatile("cp.async.bulk.tensor.3d.global.shared::cta.bulk_group [%0, {%2, %3, %4}], [%1];"
               :: "l"(tm), "r"(src), "r"(0), "r"(c1), "r"(0) : "memory");
}
__device__ __forceinline__ float ex2(float x) { float y; asm volatile("ex2.approx.ftz.f32 %0, %1;" : "=f"(y) : "f"(x)); return y; }
__device__ __forceinline__ void vadd(float& a, float b) { asm volatile("add.f32 %0, %0, %1;" : "+f"(a) : "f"(b)); }
__device__ __forceinline__ float rcp(float x) { float y; asm("rcp.approx.ftz.f32 %0, %1;" : "=f"(y) : "f"(x)); return y; }
__device__ __forceinline__ uint32_t pack_bf16(float lo, float hi) { uint32_t r; asm volatile("cvt.rn.bf16x2.f32 %0, %1, %2;" : "=r"(r) : "f"(hi), "f"(lo)); return r; }
__device__ __forceinline__ void stmatrix_x4(uint32_t a, uint32_t r0, uint32_t r1, uint32_t r2, uint32_t r3) {
  asm volatile("stmatrix.sync.aligned.m8n8.x4.shared.b16 [%0], {%1, %2, %3, %4};" :: "r"(a), "r"(r0), "r"(r1), "r"(r2), "r"(r3) : "memory");
}

struct Maps { CUtensorMap q, k, v, o, pq, pk, pv; };

template <int CL>
__global__ void __launch_bounds__(NTHREADS, 1)
mha_fwd_kernel(const __grid_constant__ Maps tm, int unit0, int tiles_base, int tiles_rem, int nclusters, int dyn0, int dyn_count) {
  extern __shared__ __align__(1024) char smem_raw[];
  const uint32_t sb = (uint32_t)__cvta_generic_to_shared(smem_raw);
  const uint32_t sBar = sb + OFF_BAR;
  const int tid = threadIdx.x;
  const int warp = __shfl_sync(0xffffffffu, tid >> 5, 0), lane = tid & 31;
  const int rank = blockIdx.x & (CL - 1);
  const int cluster_id = blockIdx.x / CL;
  if (CL == 4) asm volatile("griddepcontrol.launch_dependents;");
  const int nstatic = tiles_base + (cluster_id < tiles_rem ? 1 : 0);
  auto qrow_of = [&](int t) {
    if (t < nstatic) return (unit0 + cluster_id + t * nclusters) * (128 * CL) + rank * 128;
    if (t > nstatic || dyn_count == 0) return -1;
    mbar_wait(sBar + BAR_DYN, 0);
    const int u = lds_volatile(sBar + W_DYN);
    return u < 0 ? -1 : u * (128 * CL) + rank * 128;
  };

  uint64_t pol_first;
  asm volatile("createpolicy.fractional.L2::evict_first.b64 %0, 1.0;" : "=l"(pol_first));
  if (tid == 64) {
    if ((sb & 0xFFFFFF) != SMEM_BASE) __trap();
    for (int i = 0; i < 8; i++) mbar_init(sBar + BAR_QF + 8 * i, 1);
    for (int i = 0; i < 2; i++) mbar_init(sBar + BAR_QE + 8 * i, 1);
    asm volatile("fence.mbarrier_init.release.cluster;" ::: "memory");
    asm volatile("fence.proxy.async.shared::cta;" ::: "memory");
    #pragma unroll
    for (int c = 0; c < 4; c++) {
      mbar_expect(sBar + BAR_QF + 8 * c, 8192);
      tma_load_3d(sb + OFF_Q + c * 8192, &tm.q, qrow_of(0), c, sBar + BAR_QF + 8 * c, pol_first);
    }
  }
  if (tid == 96) {
    #pragma unroll
    for (int i = 0; i < 4 / CL; i++)
      asm volatile("cp.async.bulk.prefetch.tensor.3d.L2.global [%0, {%1, %2, %3}];"
                   :: "l"(&tm.k), "r"(0), "r"(qrow_of(0) & ~(SEQ - 1)), "r"(i * CL + rank) : "memory");
  }
  if (tid == 0) {
    asm volatile("st.shared.u32 [%0], %1;" :: "r"(sBar + W_PROG), "r"(0) : "memory");
    for (int i = 0; i < 4; i++) {
      mbar_init(sBar + BAR_KF + 8 * i, 1); mbar_init(sBar + BAR_KE + 8 * i, 2 * CL);
      mbar_init(sBar + BAR_VF + 8 * i, 1); mbar_init(sBar + BAR_VE + 8 * i, 2 * CL);
    }
    for (int i = 0; i < PF_INFLIGHT; i++) mbar_init(sBar + BAR_PF + 8 * i, 1);
    mbar_init(sBar + BAR_DYN, 1);
    for (int i = 0; i < 4; i++) { mbar_expect(sBar + BAR_KF + 8 * i, 16384); mbar_expect(sBar + BAR_VF + 8 * i, 16384); }
    mbar_expect(sBar + BAR_DYN, 4);
    asm volatile("fence.mbarrier_init.release.cluster;" ::: "memory");
  }
  if (tid == 32) {
    asm volatile("prefetch.tensormap [%0];" :: "l"(&tm.v) : "memory");
    asm volatile("prefetch.tensormap [%0];" :: "l"(&tm.o) : "memory");
  }
  cluster_arrive();
  cluster_wait();

  if (warp < 4) {
    asm volatile("setmaxnreg.dec.sync.aligned.u32 24;");
    if (warp < 2) {
      uint64_t pol = pol_first;
      if (CL == 2) asm volatile("createpolicy.fractional.L2::evict_unchanged.b64 %0, 1.0;" : "=l"(pol));
      const CUtensorMap* tmap = warp ? &tm.v : &tm.k;
      const uint32_t bE = sBar + (warp ? BAR_VE : BAR_KE), bF = sBar + (warp ? BAR_VF : BAR_KF);
      const uint32_t dst = sb + (warp ? OFF_V : OFF_K);
      uint32_t ph = 1;
      if (warp) mbar_wait(sBar + BAR_QF + 24, 0);
      for (int t = 0;; t++) {
        const int qrow = qrow_of(t);
        if (qrow < 0) break;
        const int row0 = qrow & ~(SEQ - 1);
        #pragma unroll 1
        for (int j = 0; j < 4; j++) {
          #pragma unroll
          for (int i = 0; i < 4 / CL; i++) {
            const int c = i * CL + rank;
            mbar_wait(bE + 8 * c, ph);
            if (elect_one()) {
              tma_load_3d_mc(dst + c * 16384, tmap, row0 + j * 128 + (warp ? c * 32 : 0), warp ? 0 : c, bF + 8 * c, (1 << CL) - 1, pol);
              if (warp && i == 0) asm volatile("st.volatile.shared.u32 [%0], %1;" :: "r"(sBar + W_PROG), "r"(t * 4 + j + 1) : "memory");
            }
          }
          ph ^= 1;
        }
      }
    } else if (warp == 2) {
      uint32_t ph = 1;
      mbar_wait(sBar + BAR_QF, 0);
      for (int t = 0;; t++) {
        const int qrow = qrow_of(t);
        if (qrow < 0) break;
        #pragma unroll 1
        for (int w = (t == 0 ? 1 : 0); w < 2; w++) {
          mbar_wait(sBar + BAR_QE + 8 * w, ph);
          if (elect_one()) {
            #pragma unroll
            for (int c = 0; c < 4; c++) {
              mbar_expect(sBar + BAR_QF + 32 * w + 8 * c, 8192);
              tma_load_3d(sb + OFF_Q + w * 32768 + c * 8192, &tm.q, qrow + w * 64, c, sBar + BAR_QF + 32 * w + 8 * c, pol_first);
            }
          }
        }
        ph ^= 1;
      }
    } else {
      uint32_t slot = 0, pph = 1;
      auto piece = [&](const CUtensorMap* tp, int line) {
        const uint32_t bar = sBar + BAR_PF + 8 * slot;
        mbar_wait(bar, pph);
        if (elect_one()) {
          mbar_expect(bar, 2048);
          asm volatile("cp.async.bulk.tensor.2d.shared::cluster.global.mbarrier::complete_tx::bytes [%0], [%1, {%3, %4}], [%2];"
                       :: "r"(sBar + OFF_PFDST), "l"(tp), "r"(bar), "r"(0), "r"(line) : "memory");
        }
        if (++slot == PF_INFLIGHT) { slot = 0; pph ^= 1; }
      };
      mbar_wait(sBar + BAR_QF + 56, 0);
      int qrow = qrow_of(0);
      #pragma unroll 1
      for (int g = 1;; g++) {
        if ((g & 3) == 0) { qrow = qrow_of(g >> 2); if (qrow < 0) break; }
        int prog, it = 0;
        while ((prog = lds_volatile(sBar + W_PROG)) <= g - PF_DIST) {
          __nanosleep(100);
          if (++it > (1 << 24)) __trap();
        }
        if (g == 4 * nstatic - 1 && dyn_count > 0 && rank == 0) {
          int u = 0;
          if (lane == 0) { const int tk = (int)atomicInc(&g_ticket, (unsigned)nclusters - 1); u = tk < dyn_count ? dyn0 + tk : -1; }
          u = __shfl_sync(0xffffffffu, u, 0);
          if (lane < CL)
            asm volatile("st.async.shared::cluster.mbarrier::complete_tx::bytes.u32 [%0], %1, [%2];"
                         :: "r"(mapa(sBar + W_DYN, lane)), "r"(u), "r"(mapa(sBar + BAR_DYN, lane)) : "memory");
          __syncwarp();
        }
        if (prog > g) continue;
        const int kline = ((qrow & ~(SEQ - 1)) + (g & 3) * 128) * 4 + (qrow & (SEQ - 1));
        if ((g & 3) == 0) {
          piece(&tm.pq, qrow * 4); piece(&tm.pq, qrow * 4 + 128);
          piece(&tm.pk, kline);
          piece(&tm.pq, qrow * 4 + 256); piece(&tm.pq, qrow * 4 + 384);
        } else {
          piece(&tm.pk, kline);
        }
        piece(&tm.pv, kline);
      }
      #pragma unroll 1
      for (int i = 0; i < PF_INFLIGHT; i++) {
        mbar_wait(sBar + BAR_PF + 8 * slot, pph);
        if (++slot == PF_INFLIGHT) { slot = 0; pph ^= 1; }
      }
    }
    cluster_arrive();
    cluster_wait();
  } else {
    asm volatile("setmaxnreg.inc.sync.aligned.u32 240;");
    const int w = (warp >> 2) - 1;
    const int wi = warp & 3;
    const int tid_in_wg = tid & 127;
    constexpr float cs = 0.0625f * 1.4426950408889634f;
    constexpr float TAU_RAW = 8.0f / cs;
    const uint32_t remBar = mapa(sBar, wi & (CL - 1)) + 8 * wi;
    const bool armer = (w == 0) && (wi == 3) && (lane == 0);
    const uint32_t descQ = DESC_Q + w * (32768 >> 4);
    const uint32_t sO = sb + OFF_O + (w * 4 + wi) * 4096;
    const uint32_t sO_lane = sO + (lane & 7) * 128;
    const uint32_t sxor = ((lane >> 3) ^ (lane & 7)) << 4;

    float o[128];
    float s[64];
    uint32_t p[32];
    uint32_t kvph = 0, qph = 0;
    float m0 = 0.f, m1 = 0.f, l0 = 0.f, l1 = 0.f;
    int th0 = 0, th1 = 0;
    int orow_prev = 0;
    if (w == 1) bar_arrive(1, 256);

    auto pack_half = [&](uint32_t (&r)[32], int h) {
      const float inv = h ? l1 : l0;
      #pragma unroll
      for (int i = 0; i < 32; i++) r[i] = pack_bf16(o[4 * i + 2 * h] * inv, o[4 * i + 2 * h + 1] * inv);
    };
    auto stage_half = [&](const uint32_t (&r)[32], uint32_t off, bool wait) {
      if (wait) {
        if (lane == 0) asm volatile("cp.async.bulk.wait_group.read 0;" ::: "memory");
        __syncwarp();
      }
      #pragma unroll
      for (int q = 0; q < 8; q++)
        stmatrix_x4(sO_lane + off + (q >> 1) * 1024 + (sxor ^ ((q & 1) << 6)), r[4 * q], r[4 * q + 1], r[4 * q + 2], r[4 * q + 3]);
    };
    auto flush_half = [&](int h, uint32_t off) {
      asm volatile("fence.proxy.async.shared::cta;" ::: "memory");
      __syncwarp();
      if (lane == 0) {
        tma_store_3d(&tm.o, sO + off, orow_prev + 8 * h);
        asm volatile("cp.async.bulk.commit_group;" ::: "memory");
      }
    };

    auto block = [&](auto first_tag, int t, int j) {
      constexpr bool FIRST = decltype(first_tag)::value;
      uint32_t ob[32];
      #pragma unroll
      for (int i = 0; i < 64; i++) asm volatile("" : "=f"(s[i]));
      bar_sync(1 + w, 256);
      #pragma unroll
      for (int c = 0; c < 4; c++) {
        if (FIRST) mbar_wait(sBar + BAR_QF + 32 * w + 8 * c, qph);
        mbar_wait(sBar + BAR_KF + 8 * c, kvph);
        if (armer) mbar_expect(sBar + BAR_KF + 8 * c, 16384);
        wg_fence();
        if (c == 0) wgmma_qk<0>(s, descQ, DESC_K);
        else wgmma_qk<1>(s, descQ + ((c * 8192) >> 4), DESC_K + ((c * 16384) >> 4));
        #pragma unroll
        for (int kk = 1; kk < 4; kk++)
          wgmma_qk<1>(s, descQ + ((c * 8192 + kk * 32) >> 4), DESC_K + ((c * 16384 + kk * 32) >> 4));
        wg_commit();
        if (FIRST && c == 1) {
          if (t > 0) flush_half(0, 0);
          wg_wait<2>();
          pack_half(ob, 1);
        }
      }
      bar_arrive(2 - w, 256);
      if (FIRST && t > 0) stage_half(ob, 0, true);
      wg_wait<3>(); if (tid_in_wg == 0) mbar_arrive_cluster(remBar + BAR_KE);
      wg_wait<2>(); if (tid_in_wg == 32) mbar_arrive_cluster(remBar + BAR_KE);
      wg_wait<1>(); if (tid_in_wg == 64) mbar_arrive_cluster(remBar + BAR_KE);
      wg_wait<0>(); if (tid_in_wg == 96) mbar_arrive_cluster(remBar + BAR_KE);
      if (!FIRST && j == 3 && tid_in_wg == 64) mbar_arrive(sBar + BAR_QE + 8 * w);

      bool refresh = FIRST;
      if (!FIRST) {
        int a0 = __vimax3_s32(__float_as_int(s[0]), __float_as_int(s[1]), __float_as_int(s[4]));
        int a1 = __vimax3_s32(__float_as_int(s[2]), __float_as_int(s[3]), __float_as_int(s[6]));
        int b0 = __vimax3_s32(__float_as_int(s[5]), __float_as_int(s[8]), __float_as_int(s[9]));
        int b1 = __vimax3_s32(__float_as_int(s[7]), __float_as_int(s[10]), __float_as_int(s[11]));
        #pragma unroll
        for (int i = 3; i < 15; i += 2) {
          a0 = __vimax3_s32(a0, __float_as_int(s[4 * i]), __float_as_int(s[4 * i + 1]));
          a1 = __vimax3_s32(a1, __float_as_int(s[4 * i + 2]), __float_as_int(s[4 * i + 3]));
          b0 = __vimax3_s32(b0, __float_as_int(s[4 * i + 4]), __float_as_int(s[4 * i + 5]));
          b1 = __vimax3_s32(b1, __float_as_int(s[4 * i + 6]), __float_as_int(s[4 * i + 7]));
        }
        a0 = __vimax3_s32(a0, __float_as_int(s[60]), __float_as_int(s[61]));
        a1 = __vimax3_s32(a1, __float_as_int(s[62]), __float_as_int(s[63]));
        refresh = __any_sync(0xffffffffu, (max(a0, b0) >= th0) || (max(a1, b1) >= th1));
      }
      if (refresh) {
        float x0 = fmaxf(s[0], s[1]), x1 = fmaxf(s[2], s[3]), y0 = fmaxf(s[4], s[5]), y1 = fmaxf(s[6], s[7]);
        #pragma unroll
        for (int i = 2; i < 16; i += 2) {
          x0 = fmaxf(x0, fmaxf(s[4 * i], s[4 * i + 1]));
          x1 = fmaxf(x1, fmaxf(s[4 * i + 2], s[4 * i + 3]));
          y0 = fmaxf(y0, fmaxf(s[4 * i + 4], s[4 * i + 5]));
          y1 = fmaxf(y1, fmaxf(s[4 * i + 6], s[4 * i + 7]));
        }
        x0 = fmaxf(x0, y0); x1 = fmaxf(x1, y1);
        x0 = fmaxf(x0, __shfl_xor_sync(0xffffffffu, x0, 1));
        x1 = fmaxf(x1, __shfl_xor_sync(0xffffffffu, x1, 1));
        x0 = fmaxf(x0, __shfl_xor_sync(0xffffffffu, x0, 2));
        x1 = fmaxf(x1, __shfl_xor_sync(0xffffffffu, x1, 2));
        if (FIRST) {
          l0 = 0.f; l1 = 0.f;
        } else {
          x0 = fmaxf(x0, m0); x1 = fmaxf(x1, m1);
          const float a0 = ex2((m0 - x0) * cs), a1 = ex2((m1 - x1) * cs);
          l0 *= a0; l1 *= a1;
          #pragma unroll
          for (int i = 0; i < 32; i++) {
            o[4 * i] *= a0; o[4 * i + 1] *= a0; o[4 * i + 2] *= a1; o[4 * i + 3] *= a1;
          }
        }
        m0 = x0; m1 = x1;
        const float t0 = x0 + TAU_RAW, t1 = x1 + TAU_RAW;
        th0 = t0 > 0.f ? __float_as_int(t0) : (int)0x80000000;
        th1 = t1 > 0.f ? __float_as_int(t1) : (int)0x80000000;
      }
      const float mc0 = -m0 * cs, mc1 = -m1 * cs;
      if (FIRST) {
        #pragma unroll
        for (int i = 0; i < 128; i++) asm volatile("" : "=f"(o[i]));
      }

      #pragma unroll
      for (int c = 0; c < 4; c++) {
        #pragma unroll
        for (int i = 4 * c; i < 4 * c + 4; i++) {
          const float e0 = ex2(fmaf(s[4 * i], cs, mc0)), e1 = ex2(fmaf(s[4 * i + 1], cs, mc0));
          const float e2 = ex2(fmaf(s[4 * i + 2], cs, mc1)), e3 = ex2(fmaf(s[4 * i + 3], cs, mc1));
          vadd(l0, e0); vadd(l1, e2); vadd(l0, e1); vadd(l1, e3);
          p[2 * i] = pack_bf16(e0, e1);
          p[2 * i + 1] = pack_bf16(e2, e3);
        }
        if (c == 0) continue;
        if (c == 1) bar_sync(1 + w + (p[15] >> 31), 256);
        #pragma unroll
        for (int cc = (c == 1 ? 0 : c); cc <= c; cc++) {
          mbar_wait(sBar + BAR_VF + 8 * cc, kvph);
          if (armer) mbar_expect(sBar + BAR_VF + 8 * cc, 16384);
          wg_fence();
          if (FIRST && cc == 0) wgmma_pv<0>(o, p[0], p[1], p[2], p[3], DESC_V);
          else wgmma_pv<1>(o, p[8 * cc], p[8 * cc + 1], p[8 * cc + 2], p[8 * cc + 3], DESC_V + ((cc * 16384) >> 4));
          wgmma_pv<1>(o, p[8 * cc + 4], p[8 * cc + 5], p[8 * cc + 6], p[8 * cc + 7], DESC_V + ((cc * 16384 + 2048) >> 4));
          wg_commit();
        }
      }
      bar_arrive(2 - w, 256);
      if (FIRST && t > 0) flush_half(1, 0);
      if (!FIRST && j == 3) {
        l0 += __shfl_xor_sync(0xffffffffu, l0, 1);
        l1 += __shfl_xor_sync(0xffffffffu, l1, 1);
        l0 += __shfl_xor_sync(0xffffffffu, l0, 2);
        l1 += __shfl_xor_sync(0xffffffffu, l1, 2);
        l0 = rcp(l0); l1 = rcp(l1);
      }
      wg_wait<3>(); if (tid_in_wg == 0) mbar_arrive_cluster(remBar + BAR_VE);
      wg_wait<2>(); if (tid_in_wg == 32) mbar_arrive_cluster(remBar + BAR_VE);
      wg_wait<1>(); if (tid_in_wg == 64) mbar_arrive_cluster(remBar + BAR_VE);
      wg_wait<0>(); if (tid_in_wg == 96) mbar_arrive_cluster(remBar + BAR_VE);
      kvph ^= 1;
    };

    #pragma unroll
    for (int i = 0; i < 128; i++) o[i] = 0.f;
    int qrow = qrow_of(0);
    for (int t = 0; qrow >= 0; t++) {
      block(TrueT{}, t, 0);
      #pragma unroll 1
      for (int j = 1; j < 4; j++) block(FalseT{}, t, j);
      qph ^= 1;
      orow_prev = qrow + w * 64 + wi * 16;
      uint32_t oa[32];
      pack_half(oa, 0);
      stage_half(oa, 0, true);
      qrow = __shfl_sync(0xffffffffu, qrow_of(t + 1), 0);
    }
    {
      const uint32_t off2 = (OFF_Q + w * 32768 + wi * 4096) - (OFF_O + (w * 4 + wi) * 4096);
      flush_half(0, 0);
      uint32_t ob[32];
      pack_half(ob, 1);
      stage_half(ob, off2, false);
      flush_half(1, off2);
    }
    if (w == 0) bar_sync(1, 256);
    if (lane == 0) asm volatile("cp.async.bulk.wait_group.read 0;" ::: "memory");
    __syncwarp();
    cluster_arrive();
    cluster_wait();
  }
}

typedef CUresult (*EncodeFn)(CUtensorMap*, CUtensorMapDataType, cuuint32_t, void*, const cuuint64_t*, const cuuint64_t*,
                             const cuuint32_t*, const cuuint32_t*, CUtensorMapInterleave, CUtensorMapSwizzle,
                             CUtensorMapL2promotion, CUtensorMapFloatOOBfill);

void make_map(EncodeFn enc, CUtensorMap* tm, void* ptr, uint32_t rows, uint32_t chunks) {
  cuuint64_t dims[3] = {64, (cuuint64_t)NHEADS * SEQ, 4};
  cuuint64_t strides[2] = {HD * 2, 128};
  cuuint32_t box[3] = {64, rows, chunks};
  cuuint32_t es[3] = {1, 1, 1};
  enc(tm, CU_TENSOR_MAP_DATA_TYPE_BFLOAT16, 3, ptr, dims, strides, box, es, CU_TENSOR_MAP_INTERLEAVE_NONE,
      CU_TENSOR_MAP_SWIZZLE_128B, CU_TENSOR_MAP_L2_PROMOTION_L2_128B, CU_TENSOR_MAP_FLOAT_OOB_FILL_NONE);
}
void make_pf_map(EncodeFn enc, CUtensorMap* tm, void* ptr) {
  cuuint64_t dims[2] = {64, (cuuint64_t)NHEADS * SEQ * 4};
  cuuint64_t strides[1] = {128};
  cuuint32_t box[2] = {8, 128};
  cuuint32_t es[2] = {1, 1};
  enc(tm, CU_TENSOR_MAP_DATA_TYPE_BFLOAT16, 2, ptr, dims, strides, box, es, CU_TENSOR_MAP_INTERLEAVE_NONE,
      CU_TENSOR_MAP_SWIZZLE_NONE, CU_TENSOR_MAP_L2_PROMOTION_L2_128B, CU_TENSOR_MAP_FLOAT_OOB_FILL_NONE);
}

}

extern "C" void kernel_launch(void* const* d_in, const int* in_sizes, int n_in, void* d_out, int out_size) {
  static EncodeFn enc = nullptr;
  static int nA = 0, nB = 0;
  cudaLaunchConfig_t cfg = {};
  cfg.blockDim = dim3(NTHREADS); cfg.dynamicSmemBytes = SMEM_BYTES; cfg.stream = cudaStreamPerThread;
  cudaLaunchAttribute at[2];
  at[0].id = cudaLaunchAttributeClusterDimension;
  at[0].val.clusterDim.x = 4; at[0].val.clusterDim.y = 1; at[0].val.clusterDim.z = 1;
  at[1].id = cudaLaunchAttributeProgrammaticStreamSerialization;
  at[1].val.programmaticStreamSerializationAllowed = 1;
  cfg.attrs = at; cfg.numAttrs = 1;
  if (!enc) {
    void* fn = nullptr;
    cudaDriverEntryPointQueryResult st;
    cudaGetDriverEntryPoint("cuTensorMapEncodeTiled", &fn, cudaEnableDefault, &st);
    enc = (EncodeFn)fn;
    cudaFuncSetAttribute(mha_fwd_kernel<2>, cudaFuncAttributeMaxDynamicSharedMemorySize, SMEM_BYTES);
    cudaFuncSetAttribute(mha_fwd_kernel<4>, cudaFuncAttributeMaxDynamicSharedMemorySize, SMEM_BYTES);
    int dev = 0, sms = 0;
    cudaGetDevice(&dev);
    cudaDeviceGetAttribute(&sms, cudaDevAttrMultiProcessorCount, dev);
    cfg.gridDim = dim3(sms & ~3);
    if (cudaOccupancyMaxActiveClusters(&nA, mha_fwd_kernel<4>, &cfg) != cudaSuccess) { (void)cudaGetLastError(); nA = 0; }
    if (nA > sms / 4) nA = sms / 4;
    if (nA > NHEADS / 2) nA = NHEADS / 2;
    nB = (sms - 4 * nA) / 2;
    if (nB > NHEADS) nB = NHEADS;
  }
  Maps tm;
  make_map(enc, &tm.q, d_in[0], 64, 1);
  make_map(enc, &tm.k, d_in[1], 128, 1);
  make_map(enc, &tm.v, d_in[2], 32, 4);
  make_map(enc, &tm.o, d_out, 8, 4);
  make_pf_map(enc, &tm.pq, d_in[0]);
  make_pf_map(enc, &tm.pk, d_in[1]);
  make_pf_map(enc, &tm.pv, d_in[2]);

  int R = 1;
  while (nA * R + (nB * R) / 2 < NHEADS) R++;
  int hB = (nB * (R - 1)) / 2;
  if (hB < NHEADS - nA * R) hB = NHEADS - nA * R;
  if (hB > NHEADS - nA * (R - 1)) hB = NHEADS - nA * (R - 1);
  const int hA = NHEADS - hB;
  if (nA > 0) {
    cfg.gridDim = dim3(4 * nA);
    cudaLaunchKernelEx(&cfg, mha_fwd_kernel<4>, tm, 0, R - 1, 0, nA, nA * (R - 1), hA - nA * (R - 1));
    cfg.numAttrs = 2;
  }
  if (hB > 0) {
    const int nb = nB < 2 * hB ? nB : 2 * hB;
    at[0].val.clusterDim.x = 2;
    cfg.gridDim = dim3(2 * nb);
    cudaLaunchKernelEx(&cfg, mha_fwd_kernel<2>, tm, 2 * hA, 2 * hB / nb, 2 * hB % nb, nb, 0, 0);
  }
}
```

```cpp
#include <cuda_runtime.h>
#include <cuda_bf16.h>
#include <cuda.h>
#include <stdint.h>

namespace {

constexpr int SEQ = 512;
constexpr int HD = 256;
constexpr int NHEADS = 256;
constexpr int NTHREADS = 384;
#define PF_DIST 2
#define PF_INFLIGHT 2
#define DYNAMIC 1

constexpr uint32_t SMEM_BASE = 1024;
constexpr uint32_t OFF_Q = 0;
constexpr uint32_t OFF_K = 65536;
constexpr uint32_t OFF_V = 131072;
constexpr uint32_t OFF_O = 196608;
constexpr uint32_t OFF_BAR = 229376;
constexpr uint32_t SMEM_BYTES = OFF_BAR + 512 + 2048;
constexpr uint32_t W_PROG = 0, W_DYN = 4, BAR_DYN = 8, BAR_QE = 16, BAR_KF = 32, BAR_KE = 64, BAR_VF = 96, BAR_VE = 128,
                   BAR_QF = 160  , BAR_PF = 256, OFF_PFDST = 512;
constexpr uint32_t DESC_Q = ((SMEM_BASE + OFF_Q) >> 4) | (1u << 16);
constexpr uint32_t DESC_K = ((SMEM_BASE + OFF_K) >> 4) | (1u << 16);
constexpr uint32_t DESC_V = ((SMEM_BASE + OFF_V) >> 4) | ((4096u >> 4) << 16);

__device__ unsigned int g_ticket;

struct TrueT { static constexpr bool value = true; };
struct FalseT { static constexpr bool value = false; };

template <int SCALE_D>
__device__ __forceinline__ void wgmma_qk(float (&d)[64], uint32_t loA, uint32_t loB) {
  asm volatile("{\n.reg .b64 da, db;\nmov.b64 da, {%64, 0x40000040};\nmov.b64 db, {%65, 0x40000040};\n"
    "wgmma.mma_async.sync.aligned.m64n128k16.f32.bf16.bf16 {%0, %1, %2, %3, %4, %5, %6, %7, %8, %9, %10, %11, %12, %13, %14, %15, %16, %17, %18, %19, %20, %21, %22, %23, %24, %25, %26, %27, %28, %29, %30, %31, %32, %33, %34, %35, %36, %37, %38, %39, %40, %41, %42, %43, %44, %45, %46, %47, %48, %49, %50, %51, %52, %53, %54, %55, %56, %57, %58, %59, %60, %61, %62, %63}, da, db, %66, 1, 1, 0, 0;\n}\n"
    : "+f"(d[0]), "+f"(d[1]), "+f"(d[2]), "+f"(d[3]), "+f"(d[4]), "+f"(d[5]), "+f"(d[6]), "+f"(d[7]), "+f"(d[8]), "+f"(d[9]), "+f"(d[10]), "+f"(d[11]), "+f"(d[12]), "+f"(d[13]), "+f"(d[14]), "+f"(d[15]), "+f"(d[16]), "+f"(d[17]), "+f"(d[18]), "+f"(d[19]), "+f"(d[20]), "+f"(d[21]), "+f"(d[22]), "+f"(d[23]), "+f"(d[24]), "+f"(d[25]), "+f"(d[26]), "+f"(d[27]), "+f"(d[28]), "+f"(d[29]), "+f"(d[30]), "+f"(d[31]), "+f"(d[32]), "+f"(d[33]), "+f"(d[34]), "+f"(d[35]), "+f"(d[36]), "+f"(d[37]), "+f"(d[38]), "+f"(d[39]), "+f"(d[40]), "+f"(d[41]), "+f"(d[42]), "+f"(d[43]), "+f"(d[44]), "+f"(d[45]), "+f"(d[46]), "+f"(d[47]), "+f"(d[48]), "+f"(d[49]), "+f"(d[50]), "+f"(d[51]), "+f"(d[52]), "+f"(d[53]), "+f"(d[54]), "+f"(d[55]), "+f"(d[56]), "+f"(d[57]), "+f"(d[58]), "+f"(d[59]), "+f"(d[60]), "+f"(d[61]), "+f"(d[62]), "+f"(d[63])
    : "r"(loA), "r"(loB), "n"(SCALE_D));
}
template <int SCALE_D>
__device__ __forceinline__ void wgmma_pv(float (&d)[128], uint32_t a0, uint32_t a1, uint32_t a2, uint32_t a3, uint32_t loB) {
  asm volatile("{\n.reg .b64 db;\nmov.b64 db, {%132, 0x40000040};\n"
    "wgmma.mma_async.sync.aligned.m64n256k16.f32.bf16.bf16 {%0, %1, %2, %3, %4, %5, %6, %7, %8, %9, %10, %11, %12, %13, %14, %15, %16, %17, %18, %19, %20, %21, %22, %23, %24, %25, %26, %27, %28, %29, %30, %31, %32, %33, %34, %35, %36, %37, %38, %39, %40, %41, %42, %43, %44, %45, %46, %47, %48, %49, %50, %51, %52, %53, %54, %55, %56, %57, %58, %59, %60, %61, %62, %63, %64, %65, %66, %67, %68, %69, %70, %71, %72, %73, %74, %75, %76, %77, %78, %79, %80, %81, %82, %83, %84, %85, %86, %87, %88, %89, %90, %91, %92, %93, %94, %95, %96, %97, %98, %99, %100, %101, %102, %103, %104, %105, %106, %107, %108, %109, %110, %111, %112, %113, %114, %115, %116, %117, %118, %119, %120, %121, %122, %123, %124, %125, %126, %127}, {%128, %129, %130, %131}, db, %133, 1, 1, 1;\n}\n"
    : "+f"(d[0]), "+f"(d[1]), "+f"(d[2]), "+f"(d[3]), "+f"(d[4]), "+f"(d[5]), "+f"(d[6]), "+f"(d[7]), "+f"(d[8]), "+f"(d[9]), "+f"(d[10]), "+f"(d[11]), "+f"(d[12]), "+f"(d[13]), "+f"(d[14]), "+f"(d[15]), "+f"(d[16]), "+f"(d[17]), "+f"(d[18]), "+f"(d[19]), "+f"(d[20]), "+f"(d[21]), "+f"(d[22]), "+f"(d[23]), "+f"(d[24]), "+f"(d[25]), "+f"(d[26]), "+f"(d[27]), "+f"(d[28]), "+f"(d[29]), "+f"(d[30]), "+f"(d[31]), "+f"(d[32]), "+f"(d[33]), "+f"(d[34]), "+f"(d[35]), "+f"(d[36]), "+f"(d[37]), "+f"(d[38]), "+f"(d[39]), "+f"(d[40]), "+f"(d[41]), "+f"(d[42]), "+f"(d[43]), "+f"(d[44]), "+f"(d[45]), "+f"(d[46]), "+f"(d[47]), "+f"(d[48]), "+f"(d[49]), "+f"(d[50]), "+f"(d[51]), "+f"(d[52]), "+f"(d[53]), "+f"(d[54]), "+f"(d[55]), "+f"(d[56]), "+f"(d[57]), "+f"(d[58]), "+f"(d[59]), "+f"(d[60]), "+f"(d[61]), "+f"(d[62]), "+f"(d[63]), "+f"(d[64]), "+f"(d[65]), "+f"(d[66]), "+f"(d[67]), "+f"(d[68]), "+f"(d[69]), "+f"(d[70]), "+f"(d[71]), "+f"(d[72]), "+f"(d[73]), "+f"(d[74]), "+f"(d[75]), "+f"(d[76]), "+f"(d[77]), "+f"(d[78]), "+f"(d[79]), "+f"(d[80]), "+f"(d[81]), "+f"(d[82]), "+f"(d[83]), "+f"(d[84]), "+f"(d[85]), "+f"(d[86]), "+f"(d[87]), "+f"(d[88]), "+f"(d[89]), "+f"(d[90]), "+f"(d[91]), "+f"(d[92]), "+f"(d[93]), "+f"(d[94]), "+f"(d[95]), "+f"(d[96]), "+f"(d[97]), "+f"(d[98]), "+f"(d[99]), "+f"(d[100]), "+f"(d[101]), "+f"(d[102]), "+f"(d[103]), "+f"(d[104]), "+f"(d[105]), "+f"(d[106]), "+f"(d[107]), "+f"(d[108]), "+f"(d[109]), "+f"(d[110]), "+f"(d[111]), "+f"(d[112]), "+f"(d[113]), "+f"(d[114]), "+f"(d[115]), "+f"(d[116]), "+f"(d[117]), "+f"(d[118]), "+f"(d[119]), "+f"(d[120]), "+f"(d[121]), "+f"(d[122]), "+f"(d[123]), "+f"(d[124]), "+f"(d[125]), "+f"(d[126]), "+f"(d[127])
    : "r"(a0), "r"(a1), "r"(a2), "r"(a3), "r"(loB), "n"(SCALE_D));
}

__device__ __forceinline__ void wg_fence() { asm volatile("wgmma.fence.sync.aligned;" ::: "memory"); }
__device__ __forceinline__ void wg_commit() { asm volatile("wgmma.commit_group.sync.aligned;" ::: "memory"); }
template <int N> __device__ __forceinline__ void wg_wait() { asm volatile("wgmma.wait_group.sync.aligned %0;" :: "n"(N) : "memory"); }

__device__ __forceinline__ void mbar_init(uint32_t a, int c) { asm volatile("mbarrier.init.shared::cta.b64 [%0], %1;" :: "r"(a), "r"(c) : "memory"); }
__device__ __forceinline__ void mbar_expect(uint32_t a, int b) { asm volatile("mbarrier.arrive.expect_tx.shared::cta.b64 _, [%0], %1;" :: "r"(a), "r"(b) : "memory"); }
__device__ __forceinline__ void mbar_arrive(uint32_t a) { asm volatile("mbarrier.arrive.shared::cta.b64 _, [%0];" :: "r"(a) : "memory"); }
__device__ __forceinline__ void mbar_arrive_cluster(uint32_t a) { asm volatile("mbarrier.arrive.shared::cluster.b64 _, [%0];" :: "r"(a) : "memory"); }
__device__ __forceinline__ void mbar_wait(uint32_t a, uint32_t ph) {
  asm volatile("{\n.reg .pred p;\n.reg .u32 cnt;\nmov.u32 cnt, 0;\n"
               "LAB_WAIT:\nmbarrier.try_wait.parity.shared::cta.b64 p, [%0], %1;\n@p bra LAB_DONE;\n"
               "add.u32 cnt, cnt, 1;\nsetp.lt.u32 p, cnt, 4194304;\n@p bra LAB_WAIT;\ntrap;\nLAB_DONE:\n}\n"
               :: "r"(a), "r"(ph) : "memory");
}
__device__ __forceinline__ void cluster_arrive() { asm volatile("barrier.cluster.arrive.relaxed.aligned;" ::: "memory"); }
__device__ __forceinline__ void cluster_wait() { asm volatile("barrier.cluster.wait.aligned;" ::: "memory"); }
__device__ __forceinline__ void bar_sync(int id, int n) { asm volatile("bar.sync %0, %1;" :: "r"(id), "r"(n) : "memory"); }
__device__ __forceinline__ void bar_arrive(int id, int n) { asm volatile("bar.arrive %0, %1;" :: "r"(id), "r"(n) : "memory"); }
__device__ __forceinline__ uint32_t mapa(uint32_t a, uint32_t cta) { uint32_t r; asm("mapa.shared::cluster.u32 %0, %1, %2;" : "=r"(r) : "r"(a), "r"(cta)); return r; }
__device__ __forceinline__ int lds_volatile(uint32_t a) { int v; asm volatile("ld.volatile.shared.u32 %0, [%1];" : "=r"(v) : "r"(a) : "memory"); return v; }
__device__ __forceinline__ bool elect_one() {
  uint32_t p;
  asm volatile("{\n.reg .pred P;\nelect.sync _|P, 0xffffffff;\nselp.b32 %0, 1, 0, P;\n}\n" : "=r"(p));
  return p != 0;
}

__device__ __forceinline__ void tma_load_3d(uint32_t dst, const CUtensorMap* tm, int c1, int c2, uint32_t bar, uint64_t pol) {
  asm volatile("cp.async.bulk.tensor.3d.shared::cluster.global.mbarrier::complete_tx::bytes.L2::cache_hint [%0], [%1, {%3, %4, %5}], [%2], %6;"
               :: "r"(dst), "l"(tm), "r"(bar), "r"(0), "r"(c1), "r"(c2), "l"(pol) : "memory");
}
__device__ __forceinline__ void tma_load_3d_mc(uint32_t dst, const CUtensorMap* tm, int c1, int c2, uint32_t bar, uint16_t mask, uint64_t pol) {
  asm volatile("cp.async.bulk.tensor.3d.shared::cluster.global.mbarrier::complete_tx::bytes.multicast::cluster.L2::cache_hint [%0], [%1, {%3, %4, %5}], [%2], %6, %7;"
               :: "r"(dst), "l"(tm), "r"(bar), "r"(0), "r"(c1), "r"(c2), "h"(mask), "l"(pol) : "memory");
}
__device__ __forceinline__ void tma_store_3d(const CUtensorMap* tm, uint32_t src, int c1) {
  asm volatile("cp.async.bulk.tensor.3d.global.shared::cta.bulk_group [%0, {%2, %3, %4}], [%1];"
               :: "l"(tm), "r"(src), "r"(0), "r"(c1), "r"(0) : "memory");
}
__device__ __forceinline__ float ex2(float x) { float y; asm volatile("ex2.approx.ftz.f32 %0, %1;" : "=f"(y) : "f"(x)); return y; }
__device__ __forceinline__ void vadd(float& a, float b) { asm volatile("add.f32 %0, %0, %1;" : "+f"(a) : "f"(b)); }
__device__ __forceinline__ float rcp(float x) { float y; asm("rcp.approx.ftz.f32 %0, %1;" : "=f"(y) : "f"(x)); return y; }
__device__ __forceinline__ uint32_t pack_bf16(float lo, float hi) { uint32_t r; asm volatile("cvt.rn.bf16x2.f32 %0, %1, %2;" : "=r"(r) : "f"(hi), "f"(lo)); return r; }
__device__ __forceinline__ void stmatrix_x4(uint32_t a, uint32_t r0, uint32_t r1, uint32_t r2, uint32_t r3) {
  asm volatile("stmatrix.sync.aligned.m8n8.x4.shared.b16 [%0], {%1, %2, %3, %4};" :: "r"(a), "r"(r0), "r"(r1), "r"(r2), "r"(r3) : "memory");
}

struct Maps { CUtensorMap q, k, v, o, pq, pk, pv; };

template <int CL>
__global__ void __launch_bounds__(NTHREADS, 1)
mha_fwd_kernel(const __grid_constant__ Maps tm, int unit0, int tiles_base, int tiles_rem, int nclusters, int dyn0, int dyn_count) {
  extern __shared__ __align__(1024) char smem_raw[];
  const uint32_t sb = (uint32_t)__cvta_generic_to_shared(smem_raw);
  const uint32_t sBar = sb + OFF_BAR;
  const int tid = threadIdx.x;
  const int warp = __shfl_sync(0xffffffffu, tid >> 5, 0), lane = tid & 31;
  const int rank = blockIdx.x & (CL - 1);
  const int cluster_id = blockIdx.x / CL;
  if (CL == 4) asm volatile("griddepcontrol.launch_dependents;");
  const int nstatic = tiles_base + (cluster_id < tiles_rem ? 1 : 0);
  auto qrow_of = [&](int t) {
    if (t < nstatic) return (unit0 + cluster_id + t * nclusters) * (128 * CL) + rank * 128;
    if (t > nstatic || dyn_count == 0) return -1;
    mbar_wait(sBar + BAR_DYN, 0);
    const int u = lds_volatile(sBar + W_DYN);
    return u < 0 ? -1 : u * (128 * CL) + rank * 128;
  };

  const int qrow0 = (unit0 + cluster_id) * (128 * CL) + rank * 128;

  uint64_t pol_first;
  asm volatile("createpolicy.fractional.L2::evict_first.b64 %0, 1.0;" : "=l"(pol_first));
  if (tid == 64) {
    if ((sb & 0xFFFFFF) != SMEM_BASE) __trap();
    for (int i = 0; i < 8; i++) mbar_init(sBar + BAR_QF + 8 * i, 1);
    for (int i = 0; i < 2; i++) mbar_init(sBar + BAR_QE + 8 * i, 1);
    asm volatile("fence.mbarrier_init.release.cluster;" ::: "memory");
    asm volatile("fence.proxy.async.shared::cta;" ::: "memory");
    #pragma unroll
    for (int c = 0; c < 4; c++) {
      mbar_expect(sBar + BAR_QF + 8 * c, 8192);
      tma_load_3d(sb + OFF_Q + c * 8192, &tm.q, qrow0, c, sBar + BAR_QF + 8 * c, pol_first);
    }
  }
  if (tid == 96) {
    #pragma unroll
    for (int i = 0; i < 4 / CL; i++)
      asm volatile("cp.async.bulk.prefetch.tensor.3d.L2.global [%0, {%1, %2, %3}];"
                   :: "l"(&tm.k), "r"(0), "r"(qrow0 & ~(SEQ - 1)), "r"(i * CL + rank) : "memory");
  }
  if (tid == 0) {
    asm volatile("st.shared.u32 [%0], %1;" :: "r"(sBar + W_PROG), "r"(0) : "memory");
    for (int i = 0; i < 4; i++) {
      mbar_init(sBar + BAR_KF + 8 * i, 1); mbar_init(sBar + BAR_KE + 8 * i, 2 * CL);
      mbar_init(sBar + BAR_VF + 8 * i, 1); mbar_init(sBar + BAR_VE + 8 * i, 2 * CL);
    }
    for (int i = 0; i < PF_INFLIGHT; i++) mbar_init(sBar + BAR_PF + 8 * i, 1);
    mbar_init(sBar + BAR_DYN, 1);
    for (int i = 0; i < 4; i++) { mbar_expect(sBar + BAR_KF + 8 * i, 16384); mbar_expect(sBar + BAR_VF + 8 * i, 16384); }
    mbar_expect(sBar + BAR_DYN, 4);
    asm volatile("fence.mbarrier_init.release.cluster;" ::: "memory");
  }
  if (tid == 32) {
    asm volatile("prefetch.tensormap [%0];" :: "l"(&tm.v) : "memory");
    asm volatile("prefetch.tensormap [%0];" :: "l"(&tm.o) : "memory");
  }
  cluster_arrive();
  cluster_wait();

  if (warp < 4) {
    asm volatile("setmaxnreg.dec.sync.aligned.u32 24;");
    if (warp < 2) {
      uint64_t pol = pol_first;
      if (CL == 2) asm volatile("createpolicy.fractional.L2::evict_unchanged.b64 %0, 1.0;" : "=l"(pol));
      const CUtensorMap* tmap = warp ? &tm.v : &tm.k;
      const uint32_t bE = sBar + (warp ? BAR_VE : BAR_KE), bF = sBar + (warp ? BAR_VF : BAR_KF);
      const uint32_t dst = sb + (warp ? OFF_V : OFF_K);
      uint32_t ph = 1;
      if (warp) mbar_wait(sBar + BAR_QF + 24, 0);
      for (int t = 0;; t++) {
        const int qrow = qrow_of(t);
        if (qrow < 0) break;
        const int row0 = qrow & ~(SEQ - 1);
        #pragma unroll 1
        for (int j = 0; j < 4; j++) {
          #pragma unroll
          for (int i = 0; i < 4 / CL; i++) {
            const int c = i * CL + rank;
            mbar_wait(bE + 8 * c, ph);
            if (elect_one()) {
              tma_load_3d_mc(dst + c * 16384, tmap, row0 + j * 128 + (warp ? c * 32 : 0), warp ? 0 : c, bF + 8 * c, (1 << CL) - 1, pol);
              if (warp && i == 0) asm volatile("st.volatile.shared.u32 [%0], %1;" :: "r"(sBar + W_PROG), "r"(t * 4 + j + 1) : "memory");
            }
          }
          ph ^= 1;
        }
      }
    } else if (warp == 2) {
      uint32_t ph = 1;
      mbar_wait(sBar + BAR_QF, 0);
      for (int t = 0;; t++) {
        const int qrow = qrow_of(t);
        if (qrow < 0) break;
        #pragma unroll 1
        for (int w = (t == 0 ? 1 : 0); w < 2; w++) {
          mbar_wait(sBar + BAR_QE + 8 * w, ph);
          if (elect_one()) {
            #pragma unroll
            for (int c = 0; c < 4; c++) {
              mbar_expect(sBar + BAR_QF + 32 * w + 8 * c, 8192);
              tma_load_3d(sb + OFF_Q + w * 32768 + c * 8192, &tm.q, qrow + w * 64, c, sBar + BAR_QF + 32 * w + 8 * c, pol_first);
            }
          }
        }
        ph ^= 1;
      }
    } else {
      uint32_t slot = 0, pph = 1;
      auto piece = [&](const CUtensorMap* tp, int line) {
        const uint32_t bar = sBar + BAR_PF + 8 * slot;
        mbar_wait(bar, pph);
        if (elect_one()) {
          mbar_expect(bar, 2048);
          asm volatile("cp.async.bulk.tensor.2d.shared::cluster.global.mbarrier::complete_tx::bytes [%0], [%1, {%3, %4}], [%2];"
                       :: "r"(sBar + OFF_PFDST), "l"(tp), "r"(bar), "r"(0), "r"(line) : "memory");
        }
        if (++slot == PF_INFLIGHT) { slot = 0; pph ^= 1; }
      };
      mbar_wait(sBar + BAR_QF + 56, 0);
      int qrow = qrow0;
      #pragma unroll 1
      for (int g = 1;; g++) {
        if ((g & 3) == 0) { qrow = qrow_of(g >> 2); if (qrow < 0) break; }
        int prog, it = 0;
        while ((prog = lds_volatile(sBar + W_PROG)) <= g - PF_DIST) {
          __nanosleep(100);
          if (++it > (1 << 24)) __trap();
        }
        if (g == 4 * nstatic - 1 && dyn_count > 0 && rank == 0) {
          int u = 0;
          if (lane == 0) { const int tk = (int)atomicInc(&g_ticket, (unsigned)nclusters - 1); u = tk < dyn_count ? dyn0 + tk : -1; }
          u = __shfl_sync(0xffffffffu, u, 0);
          if (lane < CL)
            asm volatile("st.async.shared::cluster.mbarrier::complete_tx::bytes.u32 [%0], %1, [%2];"
                         :: "r"(mapa(sBar + W_DYN, lane)), "r"(u), "r"(mapa(sBar + BAR_DYN, lane)) : "memory");
          __syncwarp();
        }
        if (prog > g) continue;
        const int kline = ((qrow & ~(SEQ - 1)) + (g & 3) * 128) * 4 + (qrow & (SEQ - 1));
        if ((g & 3) == 0) {
          piece(&tm.pq, qrow * 4); piece(&tm.pq, qrow * 4 + 128);
          piece(&tm.pk, kline);
          piece(&tm.pq, qrow * 4 + 256); piece(&tm.pq, qrow * 4 + 384);
        } else {
          piece(&tm.pk, kline);
        }
        piece(&tm.pv, kline);
      }
      #pragma unroll 1
      for (int i = 0; i < PF_INFLIGHT; i++) {
        mbar_wait(sBar + BAR_PF + 8 * slot, pph);
        if (++slot == PF_INFLIGHT) { slot = 0; pph ^= 1; }
      }
    }
    cluster_arrive();
    cluster_wait();
  } else {
    asm volatile("setmaxnreg.inc.sync.aligned.u32 240;");
    const int w = (warp >> 2) - 1;
    const int wi = warp & 3;
    const int tid_in_wg = tid & 127;
    constexpr float cs = 0.0625f * 1.4426950408889634f;
    constexpr float TAU_RAW = 8.0f / cs;
    const uint32_t remBar = mapa(sBar, wi & (CL - 1)) + 8 * wi;
    const bool armer = (w == 0) && (wi == 3) && (lane == 0);
    const uint32_t zero = (uint32_t)nclusters >> 30;
    const uint32_t descQ = DESC_Q + w * (32768 >> 4);
    const uint32_t sO = sb + OFF_O + (w * 4 + wi) * 4096;
    const uint32_t sO_lane = sO + (lane & 7) * 128;
    const uint32_t sxor = ((lane >> 3) ^ (lane & 7)) << 4;

    float o[128];
    float s[64];
    uint32_t p[32];
    uint32_t kvph = 0, qph = 0;
    float m0 = 0.f, m1 = 0.f, l0 = 0.f, l1 = 0.f;
    int th0 = 0, th1 = 0;
    int orow_prev = 0;
    if (w == 1) bar_arrive(1, 256);

    auto pack_half = [&](uint32_t (&r)[32], int h) {
      const float inv = h ? l1 : l0;
      #pragma unroll
      for (int i = 0; i < 32; i++) r[i] = pack_bf16(o[4 * i + 2 * h] * inv, o[4 * i + 2 * h + 1] * inv);
    };
    auto stage_half = [&](const uint32_t (&r)[32], uint32_t off, bool wait) {
      if (wait) {
        if (lane == 0) asm volatile("cp.async.bulk.wait_group.read 0;" ::: "memory");
        __syncwarp();
      }
      #pragma unroll
      for (int q = 0; q < 8; q++)
        stmatrix_x4(sO_lane + off + (q >> 1) * 1024 + (sxor ^ ((q & 1) << 6)), r[4 * q], r[4 * q + 1], r[4 * q + 2], r[4 * q + 3]);
    };
    auto flush_half = [&](int h, uint32_t off) {
      asm volatile("fence.proxy.async.shared::cta;" ::: "memory");
      __syncwarp();
      if (lane == 0) {
        tma_store_3d(&tm.o, sO + off, orow_prev + 8 * h);
        asm volatile("cp.async.bulk.commit_group;" ::: "memory");
      }
    };

    auto block = [&](auto first_tag, int t, int j) {
      constexpr bool FIRST = decltype(first_tag)::value;
      uint32_t ob[32];
      #pragma unroll
      for (int i = 0; i < 64; i++) asm volatile("" : "=f"(s[i]));
      bar_sync(1 + w, 256);
      #pragma unroll
      for (int c = 0; c < 4; c++) {
        if (FIRST) mbar_wait(sBar + BAR_QF + 32 * w + 8 * c, qph);
        mbar_wait(sBar + BAR_KF + 8 * c, kvph);
        if (armer) mbar_expect(sBar + BAR_KF + 8 * c, 16384);
        wg_fence();
        if (c == 0) wgmma_qk<0>(s, descQ, DESC_K);
        else wgmma_qk<1>(s, descQ + ((c * 8192) >> 4), DESC_K + ((c * 16384) >> 4));
        #pragma unroll
        for (int kk = 1; kk < 4; kk++)
          wgmma_qk<1>(s, descQ + ((c * 8192 + kk * 32) >> 4), DESC_K + ((c * 16384 + kk * 32) >> 4));
        wg_commit();
        if (FIRST && c == 1) {
          if (t > 0) flush_half(0, 0);
          wg_wait<2>();
          pack_half(ob, 1);
        }
      }
      bar_arrive(2 - w, 256);
      if (FIRST && t > 0) stage_half(ob, 0, true);
      wg_wait<3>(); if (tid_in_wg == 0) mbar_arrive_cluster(remBar + BAR_KE);
      wg_wait<2>(); if (tid_in_wg == 32) mbar_arrive_cluster(remBar + BAR_KE);
      wg_wait<1>(); if (tid_in_wg == 64) mbar_arrive_cluster(remBar + BAR_KE);
      wg_wait<0>(); if (tid_in_wg == 96) mbar_arrive_cluster(remBar + BAR_KE);
      if (!FIRST && j == 3 && tid_in_wg == 64) mbar_arrive(sBar + BAR_QE + 8 * w);

      bool refresh = FIRST;
      if (!FIRST) {
        int a0 = __vimax3_s32(__float_as_int(s[0]), __float_as_int(s[1]), __float_as_int(s[4]));
        int a1 = __vimax3_s32(__float_as_int(s[2]), __float_as_int(s[3]), __float_as_int(s[6]));
        int b0 = __vimax3_s32(__float_as_int(s[5]), __float_as_int(s[8]), __float_as_int(s[9]));
        int b1 = __vimax3_s32(__float_as_int(s[7]), __float_as_int(s[10]), __float_as_int(s[11]));
        #pragma unroll
        for (int i = 3; i < 15; i += 2) {
          a0 = __vimax3_s32(a0, __float_as_int(s[4 * i]), __float_as_int(s[4 * i + 1]));
          a1 = __vimax3_s32(a1, __float_as_int(s[4 * i + 2]), __float_as_int(s[4 * i + 3]));
          b0 = __vimax3_s32(b0, __float_as_int(s[4 * i + 4]), __float_as_int(s[4 * i + 5]));
          b1 = __vimax3_s32(b1, __float_as_int(s[4 * i + 6]), __float_as_int(s[4 * i + 7]));
        }
        a0 = __vimax3_s32(a0, __float_as_int(s[60]), __float_as_int(s[61]));
        a1 = __vimax3_s32(a1, __float_as_int(s[62]), __float_as_int(s[63]));
        refresh = __any_sync(0xffffffffu, (max(a0, b0) >= th0) || (max(a1, b1) >= th1));
      }
      if (refresh) {
        float x0 = fmaxf(s[0], s[1]), x1 = fmaxf(s[2], s[3]), y0 = fmaxf(s[4], s[5]), y1 = fmaxf(s[6], s[7]);
        #pragma unroll
        for (int i = 2; i < 16; i += 2) {
          x0 = fmaxf(x0, fmaxf(s[4 * i], s[4 * i + 1]));
          x1 = fmaxf(x1, fmaxf(s[4 * i + 2], s[4 * i + 3]));
          y0 = fmaxf(y0, fmaxf(s[4 * i + 4], s[4 * i + 5]));
          y1 = fmaxf(y1, fmaxf(s[4 * i + 6], s[4 * i + 7]));
        }
        x0 = fmaxf(x0, y0); x1 = fmaxf(x1, y1);
        x0 = fmaxf(x0, __shfl_xor_sync(0xffffffffu, x0, 1));
        x1 = fmaxf(x1, __shfl_xor_sync(0xffffffffu, x1, 1));
        x0 = fmaxf(x0, __shfl_xor_sync(0xffffffffu, x0, 2));
        x1 = fmaxf(x1, __shfl_xor_sync(0xffffffffu, x1, 2));
        if (FIRST) {
          l0 = 0.f; l1 = 0.f;
        } else {
          x0 = fmaxf(x0, m0); x1 = fmaxf(x1, m1);
          const float a0 = ex2((m0 - x0) * cs), a1 = ex2((m1 - x1) * cs);
          l0 *= a0; l1 *= a1;
          #pragma unroll
          for (int i = 0; i < 32; i++) {
            o[4 * i] *= a0; o[4 * i + 1] *= a0; o[4 * i + 2] *= a1; o[4 * i + 3] *= a1;
          }
        }
        m0 = x0; m1 = x1;
        const float t0 = x0 + TAU_RAW, t1 = x1 + TAU_RAW;
        th0 = t0 > 0.f ? __float_as_int(t0) : (int)0x80000000;
        th1 = t1 > 0.f ? __float_as_int(t1) : (int)0x80000000;
      }
      const float mc0 = -m0 * cs, mc1 = -m1 * cs;
      if (FIRST) {
        #pragma unroll
        for (int i = 0; i < 128; i++) asm volatile("" : "=f"(o[i]));
      }

      #pragma unroll
      for (int c = 0; c < 4; c++) {
        #pragma unroll
        for (int i = 4 * c; i < 4 * c + 4; i++) {
          const float e0 = ex2(fmaf(s[4 * i], cs, mc0)), e1 = ex2(fmaf(s[4 * i + 1], cs, mc0));
          const float e2 = ex2(fmaf(s[4 * i + 2], cs, mc1)), e3 = ex2(fmaf(s[4 * i + 3], cs, mc1));
          vadd(l0, e0); vadd(l1, e2); vadd(l0, e1); vadd(l1, e3);
          p[2 * i] = pack_bf16(e0, e1);
          p[2 * i + 1] = pack_bf16(e2, e3);
        }
        if (c == 0) continue;
        if (c == 1) bar_sync(1 + w + (p[15] & zero), 256);
        #pragma unroll
        for (int cc = (c == 1 ? 0 : c); cc <= c; cc++) {
          mbar_wait(sBar + BAR_VF + 8 * cc, kvph);
          if (armer) mbar_expect(sBar + BAR_VF + 8 * cc, 16384);
          wg_fence();
          if (FIRST && cc == 0) wgmma_pv<0>(o, p[0], p[1], p[2], p[3], DESC_V);
          else wgmma_pv<1>(o, p[8 * cc], p[8 * cc + 1], p[8 * cc + 2], p[8 * cc + 3], DESC_V + ((cc * 16384) >> 4));
          wgmma_pv<1>(o, p[8 * cc + 4], p[8 * cc + 5], p[8 * cc + 6], p[8 * cc + 7], DESC_V + ((cc * 16384 + 2048) >> 4));
          wg_commit();
        }
      }
      bar_arrive(2 - w, 256);
      if (FIRST && t > 0) flush_half(1, 0);
      if (!FIRST && j == 3) {
        l0 += __shfl_xor_sync(0xffffffffu, l0, 1);
        l1 += __shfl_xor_sync(0xffffffffu, l1, 1);
        l0 += __shfl_xor_sync(0xffffffffu, l0, 2);
        l1 += __shfl_xor_sync(0xffffffffu, l1, 2);
        l0 = rcp(l0); l1 = rcp(l1);
      }
      wg_wait<3>(); if (tid_in_wg == 0) mbar_arrive_cluster(remBar + BAR_VE);
      wg_wait<2>(); if (tid_in_wg == 32) mbar_arrive_cluster(remBar + BAR_VE);
      wg_wait<1>(); if (tid_in_wg == 64) mbar_arrive_cluster(remBar + BAR_VE);
      wg_wait<0>(); if (tid_in_wg == 96) mbar_arrive_cluster(remBar + BAR_VE);
      kvph ^= 1;
    };

    #pragma unroll
    for (int i = 0; i < 128; i++) o[i] = 0.f;
    int qrow = qrow0;
    for (int t = 0; qrow >= 0; t++) {
      block(TrueT{}, t, 0);
      #pragma unroll 1
      for (int j = 1; j < 4; j++) block(FalseT{}, t, j);
      qph ^= 1;
      orow_prev = qrow + w * 64 + wi * 16;
      uint32_t oa[32];
      pack_half(oa, 0);
      stage_half(oa, 0, true);
      qrow = __shfl_sync(0xffffffffu, qrow_of(t + 1), 0);
    }
    {
      const uint32_t off2 = (OFF_Q + w * 32768 + wi * 4096) - (OFF_O + (w * 4 + wi) * 4096);
      uint32_t ob[32];
      pack_half(ob, 1);
      stage_half(ob, off2, false);
      asm volatile("fence.proxy.async.shared::cta;" ::: "memory");
      __syncwarp();
      if (lane == 0) {
        tma_store_3d(&tm.o, sO, orow_prev);
        tma_store_3d(&tm.o, sO + off2, orow_prev + 8);
        asm volatile("cp.async.bulk.commit_group;" ::: "memory");
      }
    }
    if (w == 0) bar_sync(1, 256);
    if (lane == 0) asm volatile("cp.async.bulk.wait_group.read 0;" ::: "memory");
    __syncwarp();
    cluster_arrive();
    cluster_wait();
  }
}

typedef CUresult (*EncodeFn)(CUtensorMap*, CUtensorMapDataType, cuuint32_t, void*, const cuuint64_t*, const cuuint64_t*,
                             const cuuint32_t*, const cuuint32_t*, CUtensorMapInterleave, CUtensorMapSwizzle,
                             CUtensorMapL2promotion, CUtensorMapFloatOOBfill);

void make_map(EncodeFn enc, CUtensorMap* tm, void* ptr, uint32_t rows, uint32_t chunks) {
  cuuint64_t dims[3] = {64, (cuuint64_t)NHEADS * SEQ, 4};
  cuuint64_t strides[2] = {HD * 2, 128};
  cuuint32_t box[3] = {64, rows, chunks};
  cuuint32_t es[3] = {1, 1, 1};
  enc(tm, CU_TENSOR_MAP_DATA_TYPE_BFLOAT16, 3, ptr, dims, strides, box, es, CU_TENSOR_MAP_INTERLEAVE_NONE,
      CU_TENSOR_MAP_SWIZZLE_128B, CU_TENSOR_MAP_L2_PROMOTION_L2_128B, CU_TENSOR_MAP_FLOAT_OOB_FILL_NONE);
}
void make_pf_map(EncodeFn enc, CUtensorMap* tm, void* ptr) {
  cuuint64_t dims[2] = {64, (cuuint64_t)NHEADS * SEQ * 4};
  cuuint64_t strides[1] = {128};
  cuuint32_t box[2] = {8, 128};
  cuuint32_t es[2] = {1, 1};
  enc(tm, CU_TENSOR_MAP_DATA_TYPE_BFLOAT16, 2, ptr, dims, strides, box, es, CU_TENSOR_MAP_INTERLEAVE_NONE,
      CU_TENSOR_MAP_SWIZZLE_NONE, CU_TENSOR_MAP_L2_PROMOTION_L2_128B, CU_TENSOR_MAP_FLOAT_OOB_FILL_NONE);
}

}

extern "C" void kernel_launch(void* const* d_in, const int* in_sizes, int n_in, void* d_out, int out_size) {
  static EncodeFn enc = nullptr;
  static int nA = 0, nB = 0;
  cudaLaunchConfig_t cfg = {};
  cfg.blockDim = dim3(NTHREADS); cfg.dynamicSmemBytes = SMEM_BYTES; cfg.stream = cudaStreamPerThread;
  cudaLaunchAttribute at[2];
  at[0].id = cudaLaunchAttributeClusterDimension;
  at[0].val.clusterDim.x = 4; at[0].val.clusterDim.y = 1; at[0].val.clusterDim.z = 1;
  at[1].id = cudaLaunchAttributeProgrammaticStreamSerialization;
  at[1].val.programmaticStreamSerializationAllowed = 1;
  cfg.attrs = at; cfg.numAttrs = 1;
  if (!enc) {
    void* fn = nullptr;
    cudaDriverEntryPointQueryResult st;
    cudaGetDriverEntryPoint("cuTensorMapEncodeTiled", &fn, cudaEnableDefault, &st);
    enc = (EncodeFn)fn;
    cudaFuncSetAttribute(mha_fwd_kernel<2>, cudaFuncAttributeMaxDynamicSharedMemorySize, SMEM_BYTES);
    cudaFuncSetAttribute(mha_fwd_kernel<4>, cudaFuncAttributeMaxDynamicSharedMemorySize, SMEM_BYTES);
    int dev = 0, sms = 0;
    cudaGetDevice(&dev);
    cudaDeviceGetAttribute(&sms, cudaDevAttrMultiProcessorCount, dev);
    cfg.gridDim = dim3(sms & ~3);
    if (cudaOccupancyMaxActiveClusters(&nA, mha_fwd_kernel<4>, &cfg) != cudaSuccess) { (void)cudaGetLastError(); nA = 0; }
    if (nA > sms / 4) nA = sms / 4;
    if (nA > NHEADS / 2) nA = NHEADS / 2;
    nB = (sms - 4 * nA) / 2;
    if (nB > NHEADS) nB = NHEADS;
  }
  Maps tm;
  make_map(enc, &tm.q, d_in[0], 64, 1);
  make_map(enc, &tm.k, d_in[1], 128, 1);
  make_map(enc, &tm.v, d_in[2], 32, 4);
  make_map(enc, &tm.o, d_out, 8, 4);
  make_pf_map(enc, &tm.pq, d_in[0]);
  make_pf_map(enc, &tm.pk, d_in[1]);
  make_pf_map(enc, &tm.pv, d_in[2]);

  int R = 1;
  while (nA * R + (nB * R) / 2 < NHEADS) R++;
  int hB = (nB * (R - 1)) / 2;
  if (hB < NHEADS - nA * R) hB = NHEADS - nA * R;
  if (hB > NHEADS - nA * (R - 1)) hB = NHEADS - nA * (R - 1);
  const int hA = NHEADS - hB;
  if (nA > 0) {
    cfg.gridDim = dim3(4 * nA);
    cudaLaunchKernelEx(&cfg, mha_fwd_kernel<4>, tm, 0, R - 1, 0, nA, nA * (R - 1), hA - nA * (R - 1));
    cfg.numAttrs = 2;
  }
  if (hB > 0) {
    const int nb = nB < 2 * hB ? nB : 2 * hB;
    at[0].val.clusterDim.x = 2;
    cfg.gridDim = dim3(2 * nb);
    cudaLaunchKernelEx(&cfg, mha_fwd_kernel<2>, tm, 2 * hA, 2 * hB / nb, 2 * hB % nb, nb, 0, 0);
  }
}
```

```cpp
#include <cuda_runtime.h>
#include <cuda_bf16.h>
#include <cuda.h>
#include <stdint.h>

namespace {

constexpr int SEQ = 512;
constexpr int HD = 256;
constexpr int NHEADS = 256;
constexpr int NTHREADS = 384;
#define PF_DIST 2
#define PF_INFLIGHT 2
#define DYNAMIC 1

constexpr uint32_t SMEM_BASE = 1024;
constexpr uint32_t OFF_Q = 0;
constexpr uint32_t OFF_K = 65536;
constexpr uint32_t OFF_V = 131072;
constexpr uint32_t OFF_O = 196608;
constexpr uint32_t OFF_BAR = 229376;
constexpr uint32_t SMEM_BYTES = OFF_BAR + 512 + 2048;
constexpr uint32_t W_PROG = 0, W_DYN = 4, BAR_DYN = 8, BAR_QE = 16, BAR_KF = 32, BAR_KE = 64, BAR_VF = 96, BAR_VE = 128,
                   BAR_QF = 160  , BAR_PF = 256, OFF_PFDST = 512;
constexpr uint32_t DESC_Q = ((SMEM_BASE + OFF_Q) >> 4) | (1u << 16);
constexpr uint32_t DESC_K = ((SMEM_BASE + OFF_K) >> 4) | (1u << 16);
constexpr uint32_t DESC_V = ((SMEM_BASE + OFF_V) >> 4) | ((4096u >> 4) << 16);

__device__ unsigned int g_ticket;

struct TrueT { static constexpr bool value = true; };
struct FalseT { static constexpr bool value = false; };

template <int SCALE_D>
__device__ __forceinline__ void wgmma_qk(float (&d)[64], uint32_t loA, uint32_t loB) {
  asm volatile("{\n.reg .b64 da, db;\nmov.b64 da, {%64, 0x40000040};\nmov.b64 db, {%65, 0x40000040};\n"
    "wgmma.mma_async.sync.aligned.m64n128k16.f32.bf16.bf16 {%0, %1, %2, %3, %4, %5, %6, %7, %8, %9, %10, %11, %12, %13, %14, %15, %16, %17, %18, %19, %20, %21, %22, %23, %24, %25, %26, %27, %28, %29, %30, %31, %32, %33, %34, %35, %36, %37, %38, %39, %40, %41, %42, %43, %44, %45, %46, %47, %48, %49, %50, %51, %52, %53, %54, %55, %56, %57, %58, %59, %60, %61, %62, %63}, da, db, %66, 1, 1, 0, 0;\n}\n"
    : "+f"(d[0]), "+f"(d[1]), "+f"(d[2]), "+f"(d[3]), "+f"(d[4]), "+f"(d[5]), "+f"(d[6]), "+f"(d[7]), "+f"(d[8]), "+f"(d[9]), "+f"(d[10]), "+f"(d[11]), "+f"(d[12]), "+f"(d[13]), "+f"(d[14]), "+f"(d[15]), "+f"(d[16]), "+f"(d[17]), "+f"(d[18]), "+f"(d[19]), "+f"(d[20]), "+f"(d[21]), "+f"(d[22]), "+f"(d[23]), "+f"(d[24]), "+f"(d[25]), "+f"(d[26]), "+f"(d[27]), "+f"(d[28]), "+f"(d[29]), "+f"(d[30]), "+f"(d[31]), "+f"(d[32]), "+f"(d[33]), "+f"(d[34]), "+f"(d[35]), "+f"(d[36]), "+f"(d[37]), "+f"(d[38]), "+f"(d[39]), "+f"(d[40]), "+f"(d[41]), "+f"(d[42]), "+f"(d[43]), "+f"(d[44]), "+f"(d[45]), "+f"(d[46]), "+f"(d[47]), "+f"(d[48]), "+f"(d[49]), "+f"(d[50]), "+f"(d[51]), "+f"(d[52]), "+f"(d[53]), "+f"(d[54]), "+f"(d[55]), "+f"(d[56]), "+f"(d[57]), "+f"(d[58]), "+f"(d[59]), "+f"(d[60]), "+f"(d[61]), "+f"(d[62]), "+f"(d[63])
    : "r"(loA), "r"(loB), "n"(SCALE_D));
}
template <int SCALE_D>
__device__ __forceinline__ void wgmma_pv(float (&d)[128], uint32_t a0, uint32_t a1, uint32_t a2, uint32_t a3, uint32_t loB) {
  asm volatile("{\n.reg .b64 db;\nmov.b64 db, {%132, 0x40000040};\n"
    "wgmma.mma_async.sync.aligned.m64n256k16.f32.bf16.bf16 {%0, %1, %2, %3, %4, %5, %6, %7, %8, %9, %10, %11, %12, %13, %14, %15, %16, %17, %18, %19, %20, %21, %22, %23, %24, %25, %26, %27, %28, %29, %30, %31, %32, %33, %34, %35, %36, %37, %38, %39, %40, %41, %42, %43, %44, %45, %46, %47, %48, %49, %50, %51, %52, %53, %54, %55, %56, %57, %58, %59, %60, %61, %62, %63, %64, %65, %66, %67, %68, %69, %70, %71, %72, %73, %74, %75, %76, %77, %78, %79, %80, %81, %82, %83, %84, %85, %86, %87, %88, %89, %90, %91, %92, %93, %94, %95, %96, %97, %98, %99, %100, %101, %102, %103, %104, %105, %106, %107, %108, %109, %110, %111, %112, %113, %114, %115, %116, %117, %118, %119, %120, %121, %122, %123, %124, %125, %126, %127}, {%128, %129, %130, %131}, db, %133, 1, 1, 1;\n}\n"
    : "+f"(d[0]), "+f"(d[1]), "+f"(d[2]), "+f"(d[3]), "+f"(d[4]), "+f"(d[5]), "+f"(d[6]), "+f"(d[7]), "+f"(d[8]), "+f"(d[9]), "+f"(d[10]), "+f"(d[11]), "+f"(d[12]), "+f"(d[13]), "+f"(d[14]), "+f"(d[15]), "+f"(d[16]), "+f"(d[17]), "+f"(d[18]), "+f"(d[19]), "+f"(d[20]), "+f"(d[21]), "+f"(d[22]), "+f"(d[23]), "+f"(d[24]), "+f"(d[25]), "+f"(d[26]), "+f"(d[27]), "+f"(d[28]), "+f"(d[29]), "+f"(d[30]), "+f"(d[31]), "+f"(d[32]), "+f"(d[33]), "+f"(d[34]), "+f"(d[35]), "+f"(d[36]), "+f"(d[37]), "+f"(d[38]), "+f"(d[39]), "+f"(d[40]), "+f"(d[41]), "+f"(d[42]), "+f"(d[43]), "+f"(d[44]), "+f"(d[45]), "+f"(d[46]), "+f"(d[47]), "+f"(d[48]), "+f"(d[49]), "+f"(d[50]), "+f"(d[51]), "+f"(d[52]), "+f"(d[53]), "+f"(d[54]), "+f"(d[55]), "+f"(d[56]), "+f"(d[57]), "+f"(d[58]), "+f"(d[59]), "+f"(d[60]), "+f"(d[61]), "+f"(d[62]), "+f"(d[63]), "+f"(d[64]), "+f"(d[65]), "+f"(d[66]), "+f"(d[67]), "+f"(d[68]), "+f"(d[69]), "+f"(d[70]), "+f"(d[71]), "+f"(d[72]), "+f"(d[73]), "+f"(d[74]), "+f"(d[75]), "+f"(d[76]), "+f"(d[77]), "+f"(d[78]), "+f"(d[79]), "+f"(d[80]), "+f"(d[81]), "+f"(d[82]), "+f"(d[83]), "+f"(d[84]), "+f"(d[85]), "+f"(d[86]), "+f"(d[87]), "+f"(d[88]), "+f"(d[89]), "+f"(d[90]), "+f"(d[91]), "+f"(d[92]), "+f"(d[93]), "+f"(d[94]), "+f"(d[95]), "+f"(d[96]), "+f"(d[97]), "+f"(d[98]), "+f"(d[99]), "+f"(d[100]), "+f"(d[101]), "+f"(d[102]), "+f"(d[103]), "+f"(d[104]), "+f"(d[105]), "+f"(d[106]), "+f"(d[107]), "+f"(d[108]), "+f"(d[109]), "+f"(d[110]), "+f"(d[111]), "+f"(d[112]), "+f"(d[113]), "+f"(d[114]), "+f"(d[115]), "+f"(d[116]), "+f"(d[117]), "+f"(d[118]), "+f"(d[119]), "+f"(d[120]), "+f"(d[121]), "+f"(d[122]), "+f"(d[123]), "+f"(d[124]), "+f"(d[125]), "+f"(d[126]), "+f"(d[127])
    : "r"(a0), "r"(a1), "r"(a2), "r"(a3), "r"(loB), "n"(SCALE_D));
}

__device__ __forceinline__ void wg_fence() { asm volatile("wgmma.fence.sync.aligned;" ::: "memory"); }
__device__ __forceinline__ void wg_commit() { asm volatile("wgmma.commit_group.sync.aligned;" ::: "memory"); }
template <int N> __device__ __forceinline__ void wg_wait() { asm volatile("wgmma.wait_group.sync.aligned %0;" :: "n"(N) : "memory"); }

__device__ __forceinline__ void mbar_init(uint32_t a, int c) { asm volatile("mbarrier.init.shared::cta.b64 [%0], %1;" :: "r"(a), "r"(c) : "memory"); }
__device__ __forceinline__ void mbar_expect(uint32_t a, int b) { asm volatile("mbarrier.arrive.expect_tx.shared::cta.b64 _, [%0], %1;" :: "r"(a), "r"(b) : "memory"); }
__device__ __forceinline__ void mbar_arrive(uint32_t a) { asm volatile("mbarrier.arrive.shared::cta.b64 _, [%0];" :: "r"(a) : "memory"); }
__device__ __forceinline__ void mbar_arrive_cluster(uint32_t a) { asm volatile("mbarrier.arrive.shared::cluster.b64 _, [%0];" :: "r"(a) : "memory"); }
__device__ __forceinline__ void mbar_wait(uint32_t a, uint32_t ph) {
  asm volatile("{\n.reg .pred p;\n.reg .u32 cnt;\nmov.u32 cnt, 0;\n"
               "LAB_WAIT:\nmbarrier.try_wait.parity.shared::cta.b64 p, [%0], %1;\n@p bra LAB_DONE;\n"
               "add.u32 cnt, cnt, 1;\nsetp.lt.u32 p, cnt, 4194304;\n@p bra LAB_WAIT;\ntrap;\nLAB_DONE:\n}\n"
               :: "r"(a), "r"(ph) : "memory");
}
__device__ __forceinline__ uint32_t mbar_test4(uint32_t a, uint32_t ph) {
  uint32_t m;
  asm volatile("{\n.reg .pred p, q, r, s;\n.reg .u32 x, y;\n"
               "mbarrier.test_wait.parity.shared::cta.b64 p, [%1], %2;\n"
               "mbarrier.test_wait.parity.shared::cta.b64 q, [%1+8], %2;\n"
               "mbarrier.test_wait.parity.shared::cta.b64 r, [%1+16], %2;\n"
               "mbarrier.test_wait.parity.shared::cta.b64 s, [%1+24], %2;\n"
               "selp.b32 x, 1, 0, p;\nselp.b32 y, 2, 0, q;\nor.b32 x, x, y;\nselp.b32 y, 4, 0, r;\nor.b32 x, x, y;\n"
               "selp.b32 y, 8, 0, s;\nor.b32 %0, x, y;\n}\n"
               : "=r"(m) : "r"(a), "r"(ph) : "memory");
  return m;
}
__device__ __forceinline__ void cluster_arrive() { asm volatile("barrier.cluster.arrive.relaxed.aligned;" ::: "memory"); }
__device__ __forceinline__ void cluster_wait() { asm volatile("barrier.cluster.wait.aligned;" ::: "memory"); }
__device__ __forceinline__ void bar_sync(int id, int n) { asm volatile("bar.sync %0, %1;" :: "r"(id), "r"(n) : "memory"); }
__device__ __forceinline__ void bar_arrive(int id, int n) { asm volatile("bar.arrive %0, %1;" :: "r"(id), "r"(n) : "memory"); }
__device__ __forceinline__ uint32_t mapa(uint32_t a, uint32_t cta) { uint32_t r; asm("mapa.shared::cluster.u32 %0, %1, %2;" : "=r"(r) : "r"(a), "r"(cta)); return r; }
__device__ __forceinline__ int lds_volatile(uint32_t a) { int v; asm volatile("ld.volatile.shared.u32 %0, [%1];" : "=r"(v) : "r"(a) : "memory"); return v; }
__device__ __forceinline__ bool elect_one() {
  uint32_t p;
  asm volatile("{\n.reg .pred P;\nelect.sync _|P, 0xffffffff;\nselp.b32 %0, 1, 0, P;\n}\n" : "=r"(p));
  return p != 0;
}

__device__ __forceinline__ void tma_load_3d(uint32_t dst, const CUtensorMap* tm, int c1, int c2, uint32_t bar, uint64_t pol) {
  asm volatile("cp.async.bulk.tensor.3d.shared::cluster.global.mbarrier::complete_tx::bytes.L2::cache_hint [%0], [%1, {%3, %4, %5}], [%2], %6;"
               :: "r"(dst), "l"(tm), "r"(bar), "r"(0), "r"(c1), "r"(c2), "l"(pol) : "memory");
}
__device__ __forceinline__ void tma_load_3d_mc(uint32_t dst, const CUtensorMap* tm, int c1, int c2, uint32_t bar, uint16_t mask, uint64_t pol) {
  asm volatile("cp.async.bulk.tensor.3d.shared::cluster.global.mbarrier::complete_tx::bytes.multicast::cluster.L2::cache_hint [%0], [%1, {%3, %4, %5}], [%2], %6, %7;"
               :: "r"(dst), "l"(tm), "r"(bar), "r"(0), "r"(c1), "r"(c2), "h"(mask), "l"(pol) : "memory");
}
__device__ __forceinline__ void tma_store_3d(const CUtensorMap* tm, uint32_t src, int c1) {
  asm volatile("cp.async.bulk.tensor.3d.global.shared::cta.bulk_group [%0, {%2, %3, %4}], [%1];"
               :: "l"(tm), "r"(src), "r"(0), "r"(c1), "r"(0) : "memory");
}
__device__ __forceinline__ float ex2(float x) { float y; asm volatile("ex2.approx.ftz.f32 %0, %1;" : "=f"(y) : "f"(x)); return y; }
__device__ __forceinline__ void vadd(float& a, float b) { asm volatile("add.f32 %0, %0, %1;" : "+f"(a) : "f"(b)); }
__device__ __forceinline__ float rcp(float x) { float y; asm("rcp.approx.ftz.f32 %0, %1;" : "=f"(y) : "f"(x)); return y; }
__device__ __forceinline__ uint32_t pack_bf16(float lo, float hi) { uint32_t r; asm volatile("cvt.rn.bf16x2.f32 %0, %1, %2;" : "=r"(r) : "f"(hi), "f"(lo)); return r; }
__device__ __forceinline__ void stmatrix_x4(uint32_t a, uint32_t r0, uint32_t r1, uint32_t r2, uint32_t r3) {
  asm volatile("stmatrix.sync.aligned.m8n8.x4.shared.b16 [%0], {%1, %2, %3, %4};" :: "r"(a), "r"(r0), "r"(r1), "r"(r2), "r"(r3) : "memory");
}

struct Maps { CUtensorMap q, k, v, o, pq, pk, pv; };

template <int CL>
__global__ void __launch_bounds__(NTHREADS, 1)
mha_fwd_kernel(const __grid_constant__ Maps tm, int unit0, int tiles_base, int tiles_rem, int nclusters, int dyn0, int dyn_count) {
  extern __shared__ __align__(1024) char smem_raw[];
  const uint32_t sb = (uint32_t)__cvta_generic_to_shared(smem_raw);
  const uint32_t sBar = sb + OFF_BAR;
  const int tid = threadIdx.x;
  const int warp = __shfl_sync(0xffffffffu, tid >> 5, 0), lane = tid & 31;
  const int rank = blockIdx.x & (CL - 1);
  const int cluster_id = blockIdx.x / CL;
  if (CL == 4) asm volatile("griddepcontrol.launch_dependents;");
  const int nstatic = tiles_base + (cluster_id < tiles_rem ? 1 : 0);
  auto qrow_of = [&](int t) {
    if (t < nstatic) return (unit0 + cluster_id + t * nclusters) * (128 * CL) + rank * 128;
    if (t > nstatic || dyn_count == 0) return -1;
    mbar_wait(sBar + BAR_DYN, 0);
    const int u = lds_volatile(sBar + W_DYN);
    return u < 0 ? -1 : u * (128 * CL) + rank * 128;
  };

  const int qrow0 = (unit0 + cluster_id) * (128 * CL) + rank * 128;

  uint64_t pol_first;
  asm volatile("createpolicy.fractional.L2::evict_first.b64 %0, 1.0;" : "=l"(pol_first));
  if (tid == 64) {
    if ((sb & 0xFFFFFF) != SMEM_BASE) __trap();
    for (int i = 0; i < 8; i++) mbar_init(sBar + BAR_QF + 8 * i, 1);
    for (int i = 0; i < 2; i++) mbar_init(sBar + BAR_QE + 8 * i, 1);
    asm volatile("fence.mbarrier_init.release.cluster;" ::: "memory");
    asm volatile("fence.proxy.async.shared::cta;" ::: "memory");
    #pragma unroll
    for (int c = 0; c < 4; c++) {
      mbar_expect(sBar + BAR_QF + 8 * c, 8192);
      tma_load_3d(sb + OFF_Q + c * 8192, &tm.q, qrow0, c, sBar + BAR_QF + 8 * c, pol_first);
    }
  }
  if (tid == 96) {
    #pragma unroll
    for (int i = 0; i < 4 / CL; i++)
      asm volatile("cp.async.bulk.prefetch.tensor.3d.L2.global [%0, {%1, %2, %3}];"
                   :: "l"(&tm.k), "r"(0), "r"(qrow0 & ~(SEQ - 1)), "r"(i * CL + rank) : "memory");
  }
  if (tid == 0) {
    asm volatile("st.shared.u32 [%0], %1;" :: "r"(sBar + W_PROG), "r"(0) : "memory");
    for (int i = 0; i < 4; i++) {
      mbar_init(sBar + BAR_KF + 8 * i, 1); mbar_init(sBar + BAR_KE + 8 * i, 2 * CL);
      mbar_init(sBar + BAR_VF + 8 * i, 1); mbar_init(sBar + BAR_VE + 8 * i, 2 * CL);
    }
    for (int i = 0; i < PF_INFLIGHT; i++) mbar_init(sBar + BAR_PF + 8 * i, 1);
    mbar_init(sBar + BAR_DYN, 1);
    for (int i = 0; i < 4; i++) { mbar_expect(sBar + BAR_KF + 8 * i, 16384); mbar_expect(sBar + BAR_VF + 8 * i, 16384); }
    mbar_expect(sBar + BAR_DYN, 4);
    asm volatile("fence.mbarrier_init.release.cluster;" ::: "memory");
  }
  if (tid == 32) {
    asm volatile("prefetch.tensormap [%0];" :: "l"(&tm.v) : "memory");
    asm volatile("prefetch.tensormap [%0];" :: "l"(&tm.o) : "memory");
  }
  cluster_arrive();
  cluster_wait();

  if (warp < 4) {
    asm volatile("setmaxnreg.dec.sync.aligned.u32 24;");
    if (warp < 2) {
      uint64_t pol = pol_first;
      if (CL == 2) asm volatile("createpolicy.fractional.L2::evict_unchanged.b64 %0, 1.0;" : "=l"(pol));
      const CUtensorMap* tmap = warp ? &tm.v : &tm.k;
      const uint32_t bE = sBar + (warp ? BAR_VE : BAR_KE), bF = sBar + (warp ? BAR_VF : BAR_KF);
      const uint32_t dst = sb + (warp ? OFF_V : OFF_K);
      uint32_t ph = 1;
      if (warp) mbar_wait(sBar + BAR_QF + 24, 0);
      for (int t = 0;; t++) {
        const int qrow = qrow_of(t);
        if (qrow < 0) break;
        const int row0 = qrow & ~(SEQ - 1);
        #pragma unroll 1
        for (int j = 0; j < 4; j++) {
          #pragma unroll
          for (int i = 0; i < 4 / CL; i++) {
            const int c = i * CL + rank;
            mbar_wait(bE + 8 * c, ph);
            if (elect_one()) {
              tma_load_3d_mc(dst + c * 16384, tmap, row0 + j * 128 + (warp ? c * 32 : 0), warp ? 0 : c, bF + 8 * c, (1 << CL) - 1, pol);
              if (warp && i == 0) asm volatile("st.volatile.shared.u32 [%0], %1;" :: "r"(sBar + W_PROG), "r"(t * 4 + j + 1) : "memory");
            }
          }
          ph ^= 1;
        }
      }
    } else if (warp == 2) {
      uint32_t ph = 1;
      mbar_wait(sBar + BAR_QF, 0);
      for (int t = 0;; t++) {
        const int qrow = qrow_of(t);
        if (qrow < 0) break;
        #pragma unroll 1
        for (int w = (t == 0 ? 1 : 0); w < 2; w++) {
          mbar_wait(sBar + BAR_QE + 8 * w, ph);
          if (elect_one()) {
            #pragma unroll
            for (int c = 0; c < 4; c++) {
              mbar_expect(sBar + BAR_QF + 32 * w + 8 * c, 8192);
              tma_load_3d(sb + OFF_Q + w * 32768 + c * 8192, &tm.q, qrow + w * 64, c, sBar + BAR_QF + 32 * w + 8 * c, pol_first);
            }
          }
        }
        ph ^= 1;
      }
    } else {
      uint32_t slot = 0, pph = 1;
      auto piece = [&](const CUtensorMap* tp, int line) {
        const uint32_t bar = sBar + BAR_PF + 8 * slot;
        mbar_wait(bar, pph);
        if (elect_one()) {
          mbar_expect(bar, 2048);
          asm volatile("cp.async.bulk.tensor.2d.shared::cluster.global.mbarrier::complete_tx::bytes [%0], [%1, {%3, %4}], [%2];"
                       :: "r"(sBar + OFF_PFDST), "l"(tp), "r"(bar), "r"(0), "r"(line) : "memory");
        }
        if (++slot == PF_INFLIGHT) { slot = 0; pph ^= 1; }
      };
      mbar_wait(sBar + BAR_QF + 56, 0);
      int qrow = qrow0;
      #pragma unroll 1
      for (int g = 1;; g++) {
        if ((g & 3) == 0) { qrow = qrow_of(g >> 2); if (qrow < 0) break; }
        int prog, it = 0;
        while ((prog = lds_volatile(sBar + W_PROG)) <= g - PF_DIST) {
          __nanosleep(100);
          if (++it > (1 << 24)) __trap();
        }
        if (g == 4 * nstatic - 1 && dyn_count > 0 && rank == 0) {
          int u = 0;
          if (lane == 0) { const int tk = (int)atomicInc(&g_ticket, (unsigned)nclusters - 1); u = tk < dyn_count ? dyn0 + tk : -1; }
          u = __shfl_sync(0xffffffffu, u, 0);
          if (lane < CL)
            asm volatile("st.async.shared::cluster.mbarrier::complete_tx::bytes.u32 [%0], %1, [%2];"
                         :: "r"(mapa(sBar + W_DYN, lane)), "r"(u), "r"(mapa(sBar + BAR_DYN, lane)) : "memory");
          __syncwarp();
        }
        if (prog > g) continue;
        const int kline = ((qrow & ~(SEQ - 1)) + (g & 3) * 128) * 4 + (qrow & (SEQ - 1));
        if ((g & 3) == 0) {
          piece(&tm.pq, qrow * 4); piece(&tm.pq, qrow * 4 + 128);
          piece(&tm.pk, kline);
          piece(&tm.pq, qrow * 4 + 256); piece(&tm.pq, qrow * 4 + 384);
        } else {
          piece(&tm.pk, kline);
        }
        piece(&tm.pv, kline);
      }
      #pragma unroll 1
      for (int i = 0; i < PF_INFLIGHT; i++) {
        mbar_wait(sBar + BAR_PF + 8 * slot, pph);
        if (++slot == PF_INFLIGHT) { slot = 0; pph ^= 1; }
      }
    }
    cluster_arrive();
    cluster_wait();
  } else {
    asm volatile("setmaxnreg.inc.sync.aligned.u32 240;");
    const int w = (warp >> 2) - 1;
    const int wi = warp & 3;
    const int tid_in_wg = tid & 127;
    constexpr float cs = 0.0625f * 1.4426950408889634f;
    constexpr float TAU_RAW = 8.0f / cs;
    const uint32_t remBar = mapa(sBar, wi & (CL - 1)) + 8 * wi;
    const bool armer = (w == 0) && (wi == 3) && (lane == 0);
    const uint32_t zero = (uint32_t)nclusters >> 30;
    const uint32_t descQ = DESC_Q + w * (32768 >> 4);
    const uint32_t sO = sb + OFF_O + (w * 4 + wi) * 4096;
    uint32_t sO_a = sO + (lane & 7) * 128 + (((lane >> 3) ^ (lane & 7)) << 4), sO_b = sO_a ^ 64;
    asm volatile("mov.b32 %0, %0;\nmov.b32 %1, %1;" : "+r"(sO_a), "+r"(sO_b));

    float o[128];
    float s[64];
    uint32_t p[32];
    uint32_t kvph = 0, qph = 0;
    float m0 = 0.f, m1 = 0.f, l0 = 0.f, l1 = 0.f;
    int th0 = 0, th1 = 0;
    int orow_prev = 0, qrow = qrow0;
    uint32_t rdy0 = 0;
    uint32_t oa[32];
    float inv1 = 0.f;
    if (w == 1) bar_arrive(1, 256);

    auto pack_half = [&](uint32_t (&r)[32], int h) {
      const float inv = h ? inv1 : l0;
      #pragma unroll
      for (int i = 0; i < 32; i++) r[i] = pack_bf16(o[4 * i + 2 * h] * inv, o[4 * i + 2 * h + 1] * inv);
    };
    auto staging_free = [&]() {
      if (lane == 0) asm volatile("cp.async.bulk.wait_group.read 0;" ::: "memory");
      __syncwarp();
    };
    auto stage_half = [&](const uint32_t (&r)[32], uint32_t off) {
      #pragma unroll
      for (int q = 0; q < 8; q++)
        stmatrix_x4(((q & 1) ? sO_b : sO_a) + off + (q >> 1) * 1024, r[4 * q], r[4 * q + 1], r[4 * q + 2], r[4 * q + 3]);
    };
    auto flush_half = [&](int h) {
      asm volatile("fence.proxy.async.shared::cta;" ::: "memory");
      __syncwarp();
      if (lane == 0) {
        tma_store_3d(&tm.o, sO, orow_prev + 8 * h);
        asm volatile("cp.async.bulk.commit_group;" ::: "memory");
      }
    };

    auto block = [&](auto first_tag, int t, int j) {
      constexpr bool FIRST = decltype(first_tag)::value;
      uint32_t ob[32];
      #pragma unroll
      for (int i = 0; i < 64; i++) asm volatile("" : "=f"(s[i]));
      uint32_t rdy = FIRST ? rdy0 : mbar_test4(sBar + BAR_KF, kvph);
      bar_sync(1 + w, 256);
      #pragma unroll
      for (int c = 0; c < 4; c++) {
        if (!(rdy & (1 << c))) {
          if (FIRST) mbar_wait(sBar + BAR_QF + 32 * w + 8 * c, qph);
          mbar_wait(sBar + BAR_KF + 8 * c, kvph);
        }
        wg_fence();
        if (c == 0) wgmma_qk<0>(s, descQ, DESC_K);
        else wgmma_qk<1>(s, descQ + ((c * 8192) >> 4), DESC_K + ((c * 16384) >> 4));
        #pragma unroll
        for (int kk = 1; kk < 4; kk++)
          wgmma_qk<1>(s, descQ + ((c * 8192 + kk * 32) >> 4), DESC_K + ((c * 16384 + kk * 32) >> 4));
        wg_commit();
      }
      bar_arrive(2 - w, 256);
      if (armer) {
        #pragma unroll
        for (int c = 0; c < 4; c++) mbar_expect(sBar + BAR_KF + 8 * c, 16384);
      }
      if (FIRST && zero) stage_half(oa, 0);
      wg_wait<3>(); if (tid_in_wg == 0) mbar_arrive_cluster(remBar + BAR_KE);
      wg_wait<2>(); if (tid_in_wg == 32) mbar_arrive_cluster(remBar + BAR_KE);
      wg_wait<1>(); if (tid_in_wg == 64) mbar_arrive_cluster(remBar + BAR_KE);
      wg_wait<0>(); if (tid_in_wg == 96) mbar_arrive_cluster(remBar + BAR_KE);
      if (!FIRST && j == 3 && tid_in_wg == 64) mbar_arrive(sBar + BAR_QE + 8 * w);

      if (t > 0 && (FIRST || j == 1)) flush_half(FIRST ? 0 : 1);
      bool refresh;
      {
        int a0 = __vimax3_s32(__float_as_int(s[0]), __float_as_int(s[1]), __float_as_int(s[4]));
        int a1 = __vimax3_s32(__float_as_int(s[2]), __float_as_int(s[3]), __float_as_int(s[6]));
        int b0 = __vimax3_s32(__float_as_int(s[5]), __float_as_int(s[8]), __float_as_int(s[9]));
        int b1 = __vimax3_s32(__float_as_int(s[7]), __float_as_int(s[10]), __float_as_int(s[11]));
        #pragma unroll
        for (int i = 3; i < 15; i += 2) {
          a0 = __vimax3_s32(a0, __float_as_int(s[4 * i]), __float_as_int(s[4 * i + 1]));
          a1 = __vimax3_s32(a1, __float_as_int(s[4 * i + 2]), __float_as_int(s[4 * i + 3]));
          b0 = __vimax3_s32(b0, __float_as_int(s[4 * i + 4]), __float_as_int(s[4 * i + 5]));
          b1 = __vimax3_s32(b1, __float_as_int(s[4 * i + 6]), __float_as_int(s[4 * i + 7]));
        }
        a0 = __vimax3_s32(a0, __float_as_int(s[60]), __float_as_int(s[61]));
        a1 = __vimax3_s32(a1, __float_as_int(s[62]), __float_as_int(s[63]));
        a0 = max(a0, b0); a1 = max(a1, b1);
        if (FIRST) {
          a0 = max(a0, __shfl_xor_sync(0xffffffffu, a0, 1));
          a1 = max(a1, __shfl_xor_sync(0xffffffffu, a1, 1));
          a0 = max(a0, __shfl_xor_sync(0xffffffffu, a0, 2));
          a1 = max(a1, __shfl_xor_sync(0xffffffffu, a1, 2));
          m0 = __int_as_float(a0); m1 = __int_as_float(a1);
          th0 = __float_as_int(m0 + TAU_RAW); th1 = __float_as_int(m1 + TAU_RAW);
          l0 = 0.f; l1 = 0.f;
          refresh = __any_sync(0xffffffffu, (a0 | a1) < 0);
        } else {
          refresh = __any_sync(0xffffffffu, (a0 >= th0) || (a1 >= th1));
        }
      }
      if (refresh) {
        float x0 = fmaxf(s[0], s[1]), x1 = fmaxf(s[2], s[3]), y0 = fmaxf(s[4], s[5]), y1 = fmaxf(s[6], s[7]);
        #pragma unroll
        for (int i = 2; i < 16; i += 2) {
          x0 = fmaxf(x0, fmaxf(s[4 * i], s[4 * i + 1]));
          x1 = fmaxf(x1, fmaxf(s[4 * i + 2], s[4 * i + 3]));
          y0 = fmaxf(y0, fmaxf(s[4 * i + 4], s[4 * i + 5]));
          y1 = fmaxf(y1, fmaxf(s[4 * i + 6], s[4 * i + 7]));
        }
        x0 = fmaxf(x0, y0); x1 = fmaxf(x1, y1);
        x0 = fmaxf(x0, __shfl_xor_sync(0xffffffffu, x0, 1));
        x1 = fmaxf(x1, __shfl_xor_sync(0xffffffffu, x1, 1));
        x0 = fmaxf(x0, __shfl_xor_sync(0xffffffffu, x0, 2));
        x1 = fmaxf(x1, __shfl_xor_sync(0xffffffffu, x1, 2));
        if (!FIRST) {
          x0 = fmaxf(x0, m0); x1 = fmaxf(x1, m1);
          const float a0 = ex2((m0 - x0) * cs), a1 = ex2((m1 - x1) * cs);
          l0 *= a0; l1 *= a1;
          #pragma unroll
          for (int i = 0; i < 32; i++) {
            o[4 * i] *= a0; o[4 * i + 1] *= a0; o[4 * i + 2] *= a1; o[4 * i + 3] *= a1;
          }
        }
        m0 = x0; m1 = x1;
        const float t0 = x0 + TAU_RAW, t1 = x1 + TAU_RAW;
        th0 = t0 > 0.f ? __float_as_int(t0) : (int)0x80000000;
        th1 = t1 > 0.f ? __float_as_int(t1) : (int)0x80000000;
      }
      const float mc0 = -m0 * cs, mc1 = -m1 * cs;

      #pragma unroll
      for (int c = 0; c < 4; c++) {
        #pragma unroll
        for (int i = 4 * c; i < 4 * c + 4; i++) {
          const float e0 = ex2(fmaf(s[4 * i], cs, mc0)), e1 = ex2(fmaf(s[4 * i + 1], cs, mc0));
          const float e2 = ex2(fmaf(s[4 * i + 2], cs, mc1)), e3 = ex2(fmaf(s[4 * i + 3], cs, mc1));
          vadd(l0, e0); vadd(l1, e2); vadd(l0, e1); vadd(l1, e3);
          p[2 * i] = pack_bf16(e0, e1);
          p[2 * i + 1] = pack_bf16(e2, e3);
        }
        constexpr int C0 = FIRST ? 0 : 1;
        if (c < C0) continue;
        if (c == C0) {
          if (FIRST) {
            pack_half(ob, 1);
            #pragma unroll
            for (int i = 0; i < 128; i++) asm volatile("" : "=f"(o[i]));
          }
          rdy = mbar_test4(sBar + BAR_VF + (p[8 * C0 + 7] & zero), kvph);
          bar_sync(1 + w + (rdy & zero), 256);
        }
        #pragma unroll
        for (int cc = (c == C0 ? 0 : c); cc <= c; cc++) {
          if (!(rdy & (1 << cc))) mbar_wait(sBar + BAR_VF + 8 * cc, kvph);
          wg_fence();
          if (FIRST && cc == 0) wgmma_pv<0>(o, p[0], p[1], p[2], p[3], DESC_V);
          else wgmma_pv<1>(o, p[8 * cc], p[8 * cc + 1], p[8 * cc + 2], p[8 * cc + 3], DESC_V + ((cc * 16384) >> 4));
          wgmma_pv<1>(o, p[8 * cc + 4], p[8 * cc + 5], p[8 * cc + 6], p[8 * cc + 7], DESC_V + ((cc * 16384 + 2048) >> 4));
          wg_commit();
        }
      }
      bar_arrive(2 - w, 256);
      if (armer) {
        #pragma unroll
        for (int c = 0; c < 4; c++) mbar_expect(sBar + BAR_VF + 8 * c, 16384);
      }
      if (!FIRST && j == 3) {
        l0 += __shfl_xor_sync(0xffffffffu, l0, 1);
        l1 += __shfl_xor_sync(0xffffffffu, l1, 1);
        l0 += __shfl_xor_sync(0xffffffffu, l0, 2);
        l1 += __shfl_xor_sync(0xffffffffu, l1, 2);
        l0 = rcp(l0); inv1 = rcp(l1);
        orow_prev = qrow + w * 64 + wi * 16;
        qrow = __shfl_sync(0xffffffffu, qrow_of(t + 1), 0);
        staging_free();
      }
      wg_wait<3>(); if (tid_in_wg == 0) mbar_arrive_cluster(remBar + BAR_VE);
      wg_wait<2>(); if (tid_in_wg == 32) mbar_arrive_cluster(remBar + BAR_VE);
      if (FIRST && t > 0) { staging_free(); stage_half(ob, 0); }
      wg_wait<1>(); if (tid_in_wg == 64) mbar_arrive_cluster(remBar + BAR_VE);
      wg_wait<0>(); if (tid_in_wg == 96) mbar_arrive_cluster(remBar + BAR_VE);
      kvph ^= 1;
    };

    #pragma unroll
    for (int i = 0; i < 128; i++) o[i] = 0.f;
    #pragma unroll
    for (int i = 0; i < 32; i++) oa[i] = 0;
    for (int t = 0; qrow >= 0; t++) {
      block(TrueT{}, t, 0);
      #pragma unroll 1
      for (int j = 1; j < 4; j++) block(FalseT{}, t, j);
      qph ^= 1;
      rdy0 = mbar_test4(sBar + BAR_KF, kvph) & mbar_test4(sBar + BAR_QF + 32 * w, qph);
      pack_half(oa, 0);
      stage_half(oa, 0);
    }
    {
      const uint32_t off2 = (OFF_Q + w * 32768 + wi * 4096) - (OFF_O + (w * 4 + wi) * 4096);
      uint32_t ob[32];
      pack_half(ob, 1);
      stage_half(ob, off2);
      asm volatile("fence.proxy.async.shared::cta;" ::: "memory");
      __syncwarp();
      if (lane == 0) {
        tma_store_3d(&tm.o, sO, orow_prev);
        tma_store_3d(&tm.o, sO + off2, orow_prev + 8);
        asm volatile("cp.async.bulk.commit_group;" ::: "memory");
      }
    }
    if (w == 0) bar_sync(1, 256);
    if (lane == 0) asm volatile("cp.async.bulk.wait_group.read 0;" ::: "memory");
    __syncwarp();
    cluster_arrive();
    cluster_wait();
  }
}

typedef CUresult (*EncodeFn)(CUtensorMap*, CUtensorMapDataType, cuuint32_t, void*, const cuuint64_t*, const cuuint64_t*,
                             const cuuint32_t*, const cuuint32_t*, CUtensorMapInterleave, CUtensorMapSwizzle,
                             CUtensorMapL2promotion, CUtensorMapFloatOOBfill);

void make_map(EncodeFn enc, CUtensorMap* tm, void* ptr, uint32_t rows, uint32_t chunks) {
  cuuint64_t dims[3] = {64, (cuuint64_t)NHEADS * SEQ, 4};
  cuuint64_t strides[2] = {HD * 2, 128};
  cuuint32_t box[3] = {64, rows, chunks};
  cuuint32_t es[3] = {1, 1, 1};
  enc(tm, CU_TENSOR_MAP_DATA_TYPE_BFLOAT16, 3, ptr, dims, strides, box, es, CU_TENSOR_MAP_INTERLEAVE_NONE,
      CU_TENSOR_MAP_SWIZZLE_128B, CU_TENSOR_MAP_L2_PROMOTION_L2_128B, CU_TENSOR_MAP_FLOAT_OOB_FILL_NONE);
}
void make_pf_map(EncodeFn enc, CUtensorMap* tm, void* ptr) {
  cuuint64_t dims[2] = {64, (cuuint64_t)NHEADS * SEQ * 4};
  cuuint64_t strides[1] = {128};
  cuuint32_t box[2] = {8, 128};
  cuuint32_t es[2] = {1, 1};
  enc(tm, CU_TENSOR_MAP_DATA_TYPE_BFLOAT16, 2, ptr, dims, strides, box, es, CU_TENSOR_MAP_INTERLEAVE_NONE,
      CU_TENSOR_MAP_SWIZZLE_NONE, CU_TENSOR_MAP_L2_PROMOTION_L2_128B, CU_TENSOR_MAP_FLOAT_OOB_FILL_NONE);
}

}

extern "C" void kernel_launch(void* const* d_in, const int* in_sizes, int n_in, void* d_out, int out_size) {
  static EncodeFn enc = nullptr;
  static int nA = 0, nB = 0;
  cudaLaunchConfig_t cfg = {};
  cfg.blockDim = dim3(NTHREADS); cfg.dynamicSmemBytes = SMEM_BYTES; cfg.stream = cudaStreamPerThread;
  cudaLaunchAttribute at[2];
  at[0].id = cudaLaunchAttributeClusterDimension;
  at[0].val.clusterDim.x = 4; at[0].val.clusterDim.y = 1; at[0].val.clusterDim.z = 1;
  at[1].id = cudaLaunchAttributeProgrammaticStreamSerialization;
  at[1].val.programmaticStreamSerializationAllowed = 1;
  cfg.attrs = at; cfg.numAttrs = 1;
  if (!enc) {
    void* fn = nullptr;
    cudaDriverEntryPointQueryResult st;
    cudaGetDriverEntryPoint("cuTensorMapEncodeTiled", &fn, cudaEnableDefault, &st);
    enc = (EncodeFn)fn;
    cudaFuncSetAttribute(mha_fwd_kernel<2>, cudaFuncAttributeMaxDynamicSharedMemorySize, SMEM_BYTES);
    cudaFuncSetAttribute(mha_fwd_kernel<4>, cudaFuncAttributeMaxDynamicSharedMemorySize, SMEM_BYTES);
    int dev = 0, sms = 0;
    cudaGetDevice(&dev);
    cudaDeviceGetAttribute(&sms, cudaDevAttrMultiProcessorCount, dev);
    cfg.gridDim = dim3(sms & ~3);
    if (cudaOccupancyMaxActiveClusters(&nA, mha_fwd_kernel<4>, &cfg) != cudaSuccess) { (void)cudaGetLastError(); nA = 0; }
    if (nA > sms / 4) nA = sms / 4;
    if (nA > NHEADS / 2) nA = NHEADS / 2;
    nB = (sms - 4 * nA) / 2;
    if (nB > NHEADS) nB = NHEADS;
  }
  Maps tm;
  make_map(enc, &tm.q, d_in[0], 64, 1);
  make_map(enc, &tm.k, d_in[1], 128, 1);
  make_map(enc, &tm.v, d_in[2], 32, 4);
  make_map(enc, &tm.o, d_out, 8, 4);
  make_pf_map(enc, &tm.pq, d_in[0]);
  make_pf_map(enc, &tm.pk, d_in[1]);
  make_pf_map(enc, &tm.pv, d_in[2]);

  int R = 1;
  while (nA * R + (nB * R) / 2 < NHEADS) R++;
  int hB = (nB * (R - 1)) / 2;
  if (hB < NHEADS - nA * R) hB = NHEADS - nA * R;
  if (hB > NHEADS - nA * (R - 1)) hB = NHEADS - nA * (R - 1);
  const int hA = NHEADS - hB;
  if (nA > 0) {
    cfg.gridDim = dim3(4 * nA);
    cudaLaunchKernelEx(&cfg, mha_fwd_kernel<4>, tm, 0, R - 1, 0, nA, nA * (R - 1), hA - nA * (R - 1));
    cfg.numAttrs = 2;
  }
  if (hB > 0) {
    const int nb = nB < 2 * hB ? nB : 2 * hB;
    at[0].val.clusterDim.x = 2;
    cfg.gridDim = dim3(2 * nb);
    cudaLaunchKernelEx(&cfg, mha_fwd_kernel<2>, tm, 2 * hA, 2 * hB / nb, 2 * hB % nb, nb, 0, 0);
  }
}
```

```cpp
#include <cuda_runtime.h>
#include <cuda_bf16.h>
#include <cuda.h>
#include <stdint.h>

namespace {

constexpr int SEQ = 512;
constexpr int HD = 256;
constexpr int NHEADS = 256;
constexpr int NTHREADS = 384;
constexpr int PF_DIST = 2;
constexpr int PF_INFLIGHT = 2;

constexpr uint32_t SMEM_BASE = 1024;
constexpr uint32_t OFF_Q = 0;
constexpr uint32_t OFF_K = 65536;
constexpr uint32_t OFF_V = 131072;
constexpr uint32_t OFF_O = 196608;
constexpr uint32_t OFF_BAR = 229376;
constexpr uint32_t SMEM_BYTES = OFF_BAR + 512 + 2048;
constexpr uint32_t W_PROG = 0, W_DYN = 4, BAR_DYN = 8, BAR_QE = 16, BAR_KF = 32, BAR_KE = 64, BAR_VF = 96, BAR_VE = 128,
                   BAR_QF = 160  , BAR_PF = 256, OFF_PFDST = 512;
constexpr uint32_t DESC_Q = ((SMEM_BASE + OFF_Q) >> 4) | (1u << 16);
constexpr uint32_t DESC_K = ((SMEM_BASE + OFF_K) >> 4) | (1u << 16);
constexpr uint32_t DESC_V = ((SMEM_BASE + OFF_V) >> 4) | ((4096u >> 4) << 16);

__device__ unsigned int g_ticket;

struct TrueT { static constexpr bool value = true; };
struct FalseT { static constexpr bool value = false; };

template <int SCALE_D>
__device__ __forceinline__ void wgmma_qk(float (&d)[64], uint32_t loA, uint32_t loB) {
  asm volatile("{\n.reg .b64 da, db;\nmov.b64 da, {%64, 0x40000040};\nmov.b64 db, {%65, 0x40000040};\n"
    "wgmma.mma_async.sync.aligned.m64n128k16.f32.bf16.bf16 {%0, %1, %2, %3, %4, %5, %6, %7, %8, %9, %10, %11, %12, %13, %14, %15, %16, %17, %18, %19, %20, %21, %22, %23, %24, %25, %26, %27, %28, %29, %30, %31, %32, %33, %34, %35, %36, %37, %38, %39, %40, %41, %42, %43, %44, %45, %46, %47, %48, %49, %50, %51, %52, %53, %54, %55, %56, %57, %58, %59, %60, %61, %62, %63}, da, db, %66, 1, 1, 0, 0;\n}\n"
    : "+f"(d[0]), "+f"(d[1]), "+f"(d[2]), "+f"(d[3]), "+f"(d[4]), "+f"(d[5]), "+f"(d[6]), "+f"(d[7]), "+f"(d[8]), "+f"(d[9]), "+f"(d[10]), "+f"(d[11]), "+f"(d[12]), "+f"(d[13]), "+f"(d[14]), "+f"(d[15]), "+f"(d[16]), "+f"(d[17]), "+f"(d[18]), "+f"(d[19]), "+f"(d[20]), "+f"(d[21]), "+f"(d[22]), "+f"(d[23]), "+f"(d[24]), "+f"(d[25]), "+f"(d[26]), "+f"(d[27]), "+f"(d[28]), "+f"(d[29]), "+f"(d[30]), "+f"(d[31]), "+f"(d[32]), "+f"(d[33]), "+f"(d[34]), "+f"(d[35]), "+f"(d[36]), "+f"(d[37]), "+f"(d[38]), "+f"(d[39]), "+f"(d[40]), "+f"(d[41]), "+f"(d[42]), "+f"(d[43]), "+f"(d[44]), "+f"(d[45]), "+f"(d[46]), "+f"(d[47]), "+f"(d[48]), "+f"(d[49]), "+f"(d[50]), "+f"(d[51]), "+f"(d[52]), "+f"(d[53]), "+f"(d[54]), "+f"(d[55]), "+f"(d[56]), "+f"(d[57]), "+f"(d[58]), "+f"(d[59]), "+f"(d[60]), "+f"(d[61]), "+f"(d[62]), "+f"(d[63])
    : "r"(loA), "r"(loB), "n"(SCALE_D));
}
template <int SCALE_D>
__device__ __forceinline__ void wgmma_pv(float (&d)[128], uint32_t a0, uint32_t a1, uint32_t a2, uint32_t a3, uint32_t loB) {
  asm volatile("{\n.reg .b64 db;\nmov.b64 db, {%132, 0x40000040};\n"
    "wgmma.mma_async.sync.aligned.m64n256k16.f32.bf16.bf16 {%0, %1, %2, %3, %4, %5, %6, %7, %8, %9, %10, %11, %12, %13, %14, %15, %16, %17, %18, %19, %20, %21, %22, %23, %24, %25, %26, %27, %28, %29, %30, %31, %32, %33, %34, %35, %36, %37, %38, %39, %40, %41, %42, %43, %44, %45, %46, %47, %48, %49, %50, %51, %52, %53, %54, %55, %56, %57, %58, %59, %60, %61, %62, %63, %64, %65, %66, %67, %68, %69, %70, %71, %72, %73, %74, %75, %76, %77, %78, %79, %80, %81, %82, %83, %84, %85, %86, %87, %88, %89, %90, %91, %92, %93, %94, %95, %96, %97, %98, %99, %100, %101, %102, %103, %104, %105, %106, %107, %108, %109, %110, %111, %112, %113, %114, %115, %116, %117, %118, %119, %120, %121, %122, %123, %124, %125, %126, %127}, {%128, %129, %130, %131}, db, %133, 1, 1, 1;\n}\n"
    : "+f"(d[0]), "+f"(d[1]), "+f"(d[2]), "+f"(d[3]), "+f"(d[4]), "+f"(d[5]), "+f"(d[6]), "+f"(d[7]), "+f"(d[8]), "+f"(d[9]), "+f"(d[10]), "+f"(d[11]), "+f"(d[12]), "+f"(d[13]), "+f"(d[14]), "+f"(d[15]), "+f"(d[16]), "+f"(d[17]), "+f"(d[18]), "+f"(d[19]), "+f"(d[20]), "+f"(d[21]), "+f"(d[22]), "+f"(d[23]), "+f"(d[24]), "+f"(d[25]), "+f"(d[26]), "+f"(d[27]), "+f"(d[28]), "+f"(d[29]), "+f"(d[30]), "+f"(d[31]), "+f"(d[32]), "+f"(d[33]), "+f"(d[34]), "+f"(d[35]), "+f"(d[36]), "+f"(d[37]), "+f"(d[38]), "+f"(d[39]), "+f"(d[40]), "+f"(d[41]), "+f"(d[42]), "+f"(d[43]), "+f"(d[44]), "+f"(d[45]), "+f"(d[46]), "+f"(d[47]), "+f"(d[48]), "+f"(d[49]), "+f"(d[50]), "+f"(d[51]), "+f"(d[52]), "+f"(d[53]), "+f"(d[54]), "+f"(d[55]), "+f"(d[56]), "+f"(d[57]), "+f"(d[58]), "+f"(d[59]), "+f"(d[60]), "+f"(d[61]), "+f"(d[62]), "+f"(d[63]), "+f"(d[64]), "+f"(d[65]), "+f"(d[66]), "+f"(d[67]), "+f"(d[68]), "+f"(d[69]), "+f"(d[70]), "+f"(d[71]), "+f"(d[72]), "+f"(d[73]), "+f"(d[74]), "+f"(d[75]), "+f"(d[76]), "+f"(d[77]), "+f"(d[78]), "+f"(d[79]), "+f"(d[80]), "+f"(d[81]), "+f"(d[82]), "+f"(d[83]), "+f"(d[84]), "+f"(d[85]), "+f"(d[86]), "+f"(d[87]), "+f"(d[88]), "+f"(d[89]), "+f"(d[90]), "+f"(d[91]), "+f"(d[92]), "+f"(d[93]), "+f"(d[94]), "+f"(d[95]), "+f"(d[96]), "+f"(d[97]), "+f"(d[98]), "+f"(d[99]), "+f"(d[100]), "+f"(d[101]), "+f"(d[102]), "+f"(d[103]), "+f"(d[104]), "+f"(d[105]), "+f"(d[106]), "+f"(d[107]), "+f"(d[108]), "+f"(d[109]), "+f"(d[110]), "+f"(d[111]), "+f"(d[112]), "+f"(d[113]), "+f"(d[114]), "+f"(d[115]), "+f"(d[116]), "+f"(d[117]), "+f"(d[118]), "+f"(d[119]), "+f"(d[120]), "+f"(d[121]), "+f"(d[122]), "+f"(d[123]), "+f"(d[124]), "+f"(d[125]), "+f"(d[126]), "+f"(d[127])
    : "r"(a0), "r"(a1), "r"(a2), "r"(a3), "r"(loB), "n"(SCALE_D));
}


__device__ __forceinline__ void wg_fence() { asm volatile("wgmma.fence.sync.aligned;" ::: "memory"); }
__device__ __forceinline__ void wg_commit() { asm volatile("wgmma.commit_group.sync.aligned;" ::: "memory"); }
template <int N> __device__ __forceinline__ void wg_wait() { asm volatile("wgmma.wait_group.sync.aligned %0;" :: "n"(N) : "memory"); }

__device__ __forceinline__ void mbar_init(uint32_t a, int c) { asm volatile("mbarrier.init.shared::cta.b64 [%0], %1;" :: "r"(a), "r"(c) : "memory"); }
__device__ __forceinline__ void mbar_expect(uint32_t a, int b) { asm volatile("mbarrier.arrive.expect_tx.shared::cta.b64 _, [%0], %1;" :: "r"(a), "r"(b) : "memory"); }
__device__ __forceinline__ void mbar_arrive(uint32_t a) { asm volatile("mbarrier.arrive.shared::cta.b64 _, [%0];" :: "r"(a) : "memory"); }
__device__ __forceinline__ void mbar_arrive_cluster(uint32_t a) { asm volatile("mbarrier.arrive.shared::cluster.b64 _, [%0];" :: "r"(a) : "memory"); }
__device__ __forceinline__ void mbar_wait(uint32_t a, uint32_t ph) {
  asm volatile("{\n.reg .pred p;\n.reg .u32 cnt;\nmov.u32 cnt, 0;\n"
               "LAB_WAIT:\nmbarrier.try_wait.parity.shared::cta.b64 p, [%0], %1;\n@p bra LAB_DONE;\n"
               "add.u32 cnt, cnt, 1;\nsetp.lt.u32 p, cnt, 4194304;\n@p bra LAB_WAIT;\ntrap;\nLAB_DONE:\n}\n"
               :: "r"(a), "r"(ph) : "memory");
}
__device__ __forceinline__ uint32_t mbar_test4(uint32_t a, uint32_t ph) {
  uint32_t m;
  asm volatile("{\n.reg .pred p, q, r, s;\n.reg .u32 x, y;\n"
               "mbarrier.test_wait.parity.shared::cta.b64 p, [%1], %2;\n"
               "mbarrier.test_wait.parity.shared::cta.b64 q, [%1+8], %2;\n"
               "mbarrier.test_wait.parity.shared::cta.b64 r, [%1+16], %2;\n"
               "mbarrier.test_wait.parity.shared::cta.b64 s, [%1+24], %2;\n"
               "selp.b32 x, 1, 0, p;\nselp.b32 y, 2, 0, q;\nor.b32 x, x, y;\nselp.b32 y, 4, 0, r;\nor.b32 x, x, y;\n"
               "selp.b32 y, 8, 0, s;\nor.b32 %0, x, y;\n}\n"
               : "=r"(m) : "r"(a), "r"(ph) : "memory");
  return m;
}
__device__ __forceinline__ void cluster_arrive() { asm volatile("barrier.cluster.arrive.relaxed.aligned;" ::: "memory"); }
__device__ __forceinline__ void cluster_wait() { asm volatile("barrier.cluster.wait.aligned;" ::: "memory"); }
__device__ __forceinline__ void bar_sync(int id, int n) { asm volatile("bar.sync %0, %1;" :: "r"(id), "r"(n) : "memory"); }
__device__ __forceinline__ void bar_arrive(int id, int n) { asm volatile("bar.arrive %0, %1;" :: "r"(id), "r"(n) : "memory"); }
__device__ __forceinline__ uint32_t mapa(uint32_t a, uint32_t cta) { uint32_t r; asm("mapa.shared::cluster.u32 %0, %1, %2;" : "=r"(r) : "r"(a), "r"(cta)); return r; }
__device__ __forceinline__ int lds_volatile(uint32_t a) { int v; asm volatile("ld.volatile.shared.u32 %0, [%1];" : "=r"(v) : "r"(a) : "memory"); return v; }
__device__ __forceinline__ bool elect_one() {
  uint32_t p;
  asm volatile("{\n.reg .pred P;\nelect.sync _|P, 0xffffffff;\nselp.b32 %0, 1, 0, P;\n}\n" : "=r"(p));
  return p != 0;
}

__device__ __forceinline__ void tma_load_3d(uint32_t dst, const CUtensorMap* tm, int c1, int c2, uint32_t bar, uint64_t pol) {
  asm volatile("cp.async.bulk.tensor.3d.shared::cluster.global.mbarrier::complete_tx::bytes.L2::cache_hint [%0], [%1, {%3, %4, %5}], [%2], %6;"
               :: "r"(dst), "l"(tm), "r"(bar), "r"(0), "r"(c1), "r"(c2), "l"(pol) : "memory");
}
__device__ __forceinline__ void tma_load_3d_mc(uint32_t dst, const CUtensorMap* tm, int c1, int c2, uint32_t bar, uint16_t mask, uint64_t pol) {
  asm volatile("cp.async.bulk.tensor.3d.shared::cluster.global.mbarrier::complete_tx::bytes.multicast::cluster.L2::cache_hint [%0], [%1, {%3, %4, %5}], [%2], %6, %7;"
               :: "r"(dst), "l"(tm), "r"(bar), "r"(0), "r"(c1), "r"(c2), "h"(mask), "l"(pol) : "memory");
}
__device__ __forceinline__ void tma_store_3d(const CUtensorMap* tm, uint32_t src, int c1) {
  asm volatile("cp.async.bulk.tensor.3d.global.shared::cta.bulk_group [%0, {%2, %3, %4}], [%1];"
               :: "l"(tm), "r"(src), "r"(0), "r"(c1), "r"(0) : "memory");
}
__device__ __forceinline__ float ex2(float x) { float y; asm volatile("ex2.approx.ftz.f32 %0, %1;" : "=f"(y) : "f"(x)); return y; }
__device__ __forceinline__ void vadd(float& a, float b) { asm volatile("add.f32 %0, %0, %1;" : "+f"(a) : "f"(b)); }
__device__ __forceinline__ float rcp(float x) { float y; asm("rcp.approx.ftz.f32 %0, %1;" : "=f"(y) : "f"(x)); return y; }
__device__ __forceinline__ uint32_t pack_bf16(float lo, float hi) { uint32_t r; asm volatile("cvt.rn.bf16x2.f32 %0, %1, %2;" : "=r"(r) : "f"(hi), "f"(lo)); return r; }
__device__ __forceinline__ void stmatrix_x4(uint32_t a, uint32_t r0, uint32_t r1, uint32_t r2, uint32_t r3) {
  asm volatile("stmatrix.sync.aligned.m8n8.x4.shared.b16 [%0], {%1, %2, %3, %4};" :: "r"(a), "r"(r0), "r"(r1), "r"(r2), "r"(r3) : "memory");
}

struct Maps { CUtensorMap q, k, v, o, pq, pk, pv; };

template <int CL>
__global__ void __launch_bounds__(NTHREADS, 1)
mha_fwd_kernel(const __grid_constant__ Maps tm, int unit0, int tiles_base, int tiles_rem, int nclusters, int dyn0, int dyn_count) {
  extern __shared__ __align__(1024) char smem_raw[];
  const uint32_t sb = (uint32_t)__cvta_generic_to_shared(smem_raw);
  const uint32_t sBar = sb + OFF_BAR;
  const int tid = threadIdx.x;
  const int warp = __shfl_sync(0xffffffffu, tid >> 5, 0), lane = tid & 31;
  const int rank = blockIdx.x & (CL - 1);
  const int cluster_id = blockIdx.x / CL;
  if (CL == 4) asm volatile("griddepcontrol.launch_dependents;");
  const int nstatic = tiles_base + (cluster_id < tiles_rem ? 1 : 0);
  auto qrow_of = [&](int t) {
    if (t < nstatic) return (unit0 + cluster_id + t * nclusters) * (128 * CL) + rank * 128;
    if (t > nstatic || dyn_count == 0) return -1;
    mbar_wait(sBar + BAR_DYN, 0);
    const int u = lds_volatile(sBar + W_DYN);
    return u < 0 ? -1 : u * (128 * CL) + rank * 128;
  };

  const int qrow0 = (unit0 + cluster_id) * (128 * CL) + rank * 128;

  uint64_t pol_first;
  asm volatile("createpolicy.fractional.L2::evict_first.b64 %0, 1.0;" : "=l"(pol_first));
  if (tid == 64) {
    if ((sb & 0xFFFFFF) != SMEM_BASE) __trap();
    for (int i = 0; i < 8; i++) mbar_init(sBar + BAR_QF + 8 * i, 1);
    for (int i = 0; i < 2; i++) mbar_init(sBar + BAR_QE + 8 * i, 1);
    asm volatile("fence.mbarrier_init.release.cluster;" ::: "memory");
    asm volatile("fence.proxy.async.shared::cta;" ::: "memory");
    #pragma unroll
    for (int c = 0; c < 4; c++) {
      mbar_expect(sBar + BAR_QF + 8 * c, 8192);
      tma_load_3d(sb + OFF_Q + c * 8192, &tm.q, qrow0, c, sBar + BAR_QF + 8 * c, pol_first);
    }
  }
  if (tid == 96) {
    #pragma unroll
    for (int i = 0; i < 4 / CL; i++)
      asm volatile("cp.async.bulk.prefetch.tensor.3d.L2.global [%0, {%1, %2, %3}];"
                   :: "l"(&tm.k), "r"(0), "r"(qrow0 & ~(SEQ - 1)), "r"(i * CL + rank) : "memory");
  }
  if (tid == 0) {
    asm volatile("st.shared.u32 [%0], %1;" :: "r"(sBar + W_PROG), "r"(0) : "memory");
    for (int i = 0; i < 4; i++) {
      mbar_init(sBar + BAR_KF + 8 * i, 1); mbar_init(sBar + BAR_KE + 8 * i, 2 * CL);
      mbar_init(sBar + BAR_VF + 8 * i, 1); mbar_init(sBar + BAR_VE + 8 * i, 2 * CL);
    }
    for (int i = 0; i < PF_INFLIGHT; i++) mbar_init(sBar + BAR_PF + 8 * i, 1);
    mbar_init(sBar + BAR_DYN, 1);
    for (int i = 0; i < 4; i++) { mbar_expect(sBar + BAR_KF + 8 * i, 16384); mbar_expect(sBar + BAR_VF + 8 * i, 16384); }
    mbar_expect(sBar + BAR_DYN, 4);
    asm volatile("fence.mbarrier_init.release.cluster;" ::: "memory");
  }
  if (tid == 32) {
    asm volatile("prefetch.tensormap [%0];" :: "l"(&tm.v) : "memory");
    asm volatile("prefetch.tensormap [%0];" :: "l"(&tm.o) : "memory");
  }
  cluster_arrive();
  cluster_wait();

  if (warp < 4) {
    asm volatile("setmaxnreg.dec.sync.aligned.u32 24;");
    if (warp < 2) {
      uint64_t pol = pol_first;
      if (CL == 2) asm volatile("createpolicy.fractional.L2::evict_unchanged.b64 %0, 1.0;" : "=l"(pol));
      const CUtensorMap* tmap = warp ? &tm.v : &tm.k;
      const uint32_t bE = sBar + (warp ? BAR_VE : BAR_KE), bF = sBar + (warp ? BAR_VF : BAR_KF);
      const uint32_t dst = sb + (warp ? OFF_V : OFF_K);
      uint32_t ph = 1;
      if (warp) mbar_wait(sBar + BAR_QF + 24, 0);
      for (int t = 0;; t++) {
        const int qrow = qrow_of(t);
        if (qrow < 0) break;
        const int row0 = qrow & ~(SEQ - 1);
        #pragma unroll 1
        for (int j = 0; j < 4; j++) {
          #pragma unroll
          for (int i = 0; i < 4 / CL; i++) {
            const int c = i * CL + rank;
            mbar_wait(bE + 8 * c, ph);
            if (elect_one()) {
              tma_load_3d_mc(dst + c * 16384, tmap, row0 + j * 128 + (warp ? c * 32 : 0), warp ? 0 : c, bF + 8 * c, (1 << CL) - 1, pol);
              if (warp && i == 0) asm volatile("st.volatile.shared.u32 [%0], %1;" :: "r"(sBar + W_PROG), "r"(t * 4 + j + 1) : "memory");
            }
          }
          ph ^= 1;
        }
      }
    } else if (warp == 2) {
      uint32_t ph = 1;
      mbar_wait(sBar + BAR_QF, 0);
      for (int t = 0;; t++) {
        const int qrow = qrow_of(t);
        if (qrow < 0) break;
        #pragma unroll 1
        for (int w = (t == 0 ? 1 : 0); w < 2; w++) {
          mbar_wait(sBar + BAR_QE + 8 * w, ph);
          if (elect_one()) {
            #pragma unroll
            for (int c = 0; c < 4; c++) {
              mbar_expect(sBar + BAR_QF + 32 * w + 8 * c, 8192);
              tma_load_3d(sb + OFF_Q + w * 32768 + c * 8192, &tm.q, qrow + w * 64, c, sBar + BAR_QF + 32 * w + 8 * c, pol_first);
            }
          }
        }
        ph ^= 1;
      }
    } else {
      uint32_t slot = 0, pph = 1;
      auto piece = [&](const CUtensorMap* tp, int line) {
        const uint32_t bar = sBar + BAR_PF + 8 * slot;
        mbar_wait(bar, pph);
        if (elect_one()) {
          mbar_expect(bar, 2048);
          asm volatile("cp.async.bulk.tensor.2d.shared::cluster.global.mbarrier::complete_tx::bytes [%0], [%1, {%3, %4}], [%2];"
                       :: "r"(sBar + OFF_PFDST), "l"(tp), "r"(bar), "r"(0), "r"(line) : "memory");
        }
        if (++slot == PF_INFLIGHT) { slot = 0; pph ^= 1; }
      };
      mbar_wait(sBar + BAR_QF + 56, 0);
      int qrow = qrow0;
      #pragma unroll 1
      for (int g = 1;; g++) {
        if ((g & 3) == 0) { qrow = qrow_of(g >> 2); if (qrow < 0) break; }
        int prog, it = 0;
        while ((prog = lds_volatile(sBar + W_PROG)) <= g - PF_DIST) {
          __nanosleep(100);
          if (++it > (1 << 24)) __trap();
        }
        if (g == 4 * nstatic - 1 && dyn_count > 0 && rank == 0) {
          int u = 0;
          if (lane == 0) { const int tk = (int)atomicInc(&g_ticket, (unsigned)nclusters - 1); u = tk < dyn_count ? dyn0 + tk : -1; }
          u = __shfl_sync(0xffffffffu, u, 0);
          if (lane < CL)
            asm volatile("st.async.shared::cluster.mbarrier::complete_tx::bytes.u32 [%0], %1, [%2];"
                         :: "r"(mapa(sBar + W_DYN, lane)), "r"(u), "r"(mapa(sBar + BAR_DYN, lane)) : "memory");
          __syncwarp();
        }
        if (prog > g) continue;
        const int kline = ((qrow & ~(SEQ - 1)) + (g & 3) * 128) * 4 + (qrow & (SEQ - 1));
        if ((g & 3) == 0) {
          piece(&tm.pq, qrow * 4); piece(&tm.pq, qrow * 4 + 128);
          piece(&tm.pk, kline);
          piece(&tm.pq, qrow * 4 + 256); piece(&tm.pq, qrow * 4 + 384);
        } else {
          piece(&tm.pk, kline);
        }
        piece(&tm.pv, kline);
      }
      #pragma unroll 1
      for (int i = 0; i < PF_INFLIGHT; i++) {
        mbar_wait(sBar + BAR_PF + 8 * slot, pph);
        if (++slot == PF_INFLIGHT) { slot = 0; pph ^= 1; }
      }
    }
    cluster_arrive();
    cluster_wait();
  } else {
    asm volatile("setmaxnreg.inc.sync.aligned.u32 240;");
    const int w = (warp >> 2) - 1;
    const int wi = warp & 3;
    const int tid_in_wg = tid & 127;
    constexpr float cs = 0.0625f * 1.4426950408889634f;
    constexpr float TAU_RAW = 8.0f / cs;
    const uint32_t remBar = mapa(sBar, wi & (CL - 1)) + 8 * wi;
    const bool armer = (w == 0) && (wi == 3) && (lane == 0);
    const uint32_t zero = (uint32_t)nclusters >> 30;
    const uint32_t descQ = DESC_Q + w * (32768 >> 4);
    const uint32_t sO = sb + OFF_O + (w * 4 + wi) * 4096;
    uint32_t sO_a = sO + (lane & 7) * 128 + (((lane >> 3) ^ (lane & 7)) << 4), sO_b = sO_a ^ 64;
    asm volatile("mov.b32 %0, %0;\nmov.b32 %1, %1;" : "+r"(sO_a), "+r"(sO_b));

    float o[128];
    float s[64];
    uint32_t p[32];
    uint32_t kvph = 0, qph = 0;
    float m0 = 0.f, m1 = 0.f, l0 = 0.f, l1 = 0.f;
    int th0 = 0, th1 = 0;
    int orow_prev = 0, qrow = qrow0;
    uint32_t rdy0 = 0;
    uint32_t oa[32];
    float inv1 = 0.f;
    if (w == 1) bar_arrive(1, 256);

    auto pack_half = [&](uint32_t (&r)[32], int h) {
      const float inv = h ? inv1 : l0;
      #pragma unroll
      for (int i = 0; i < 32; i++) r[i] = pack_bf16(o[4 * i + 2 * h] * inv, o[4 * i + 2 * h + 1] * inv);
    };
    auto staging_free = [&]() {
      if (lane == 0) asm volatile("cp.async.bulk.wait_group.read 0;" ::: "memory");
      __syncwarp();
    };
    auto stage_half = [&](const uint32_t (&r)[32], uint32_t off) {
      #pragma unroll
      for (int q = 0; q < 8; q++)
        stmatrix_x4(((q & 1) ? sO_b : sO_a) + off + (q >> 1) * 1024, r[4 * q], r[4 * q + 1], r[4 * q + 2], r[4 * q + 3]);
    };
    auto flush_half = [&](int h) {
      asm volatile("fence.proxy.async.shared::cta;" ::: "memory");
      __syncwarp();
      if (lane == 0) {
        tma_store_3d(&tm.o, sO, orow_prev + 8 * h);
        asm volatile("cp.async.bulk.commit_group;" ::: "memory");
      }
    };

    auto block = [&](auto first_tag, int t, int j) {
      constexpr bool FIRST = decltype(first_tag)::value;
      uint32_t ob[32];
      #pragma unroll
      for (int i = 0; i < 64; i++) asm volatile("" : "=f"(s[i]));
      uint32_t rdy = FIRST ? rdy0 : mbar_test4(sBar + BAR_KF, kvph);
      bar_sync(1 + w, 256);
      #pragma unroll
      for (int c = 0; c < 4; c++) {
        if (!(rdy & (1 << c))) {
          if (FIRST) mbar_wait(sBar + BAR_QF + 32 * w + 8 * c, qph);
          mbar_wait(sBar + BAR_KF + 8 * c, kvph);
        }
        wg_fence();
        if (c == 0) wgmma_qk<0>(s, descQ, DESC_K);
        else wgmma_qk<1>(s, descQ + ((c * 8192) >> 4), DESC_K + ((c * 16384) >> 4));
        #pragma unroll
        for (int kk = 1; kk < 4; kk++)
          wgmma_qk<1>(s, descQ + ((c * 8192 + kk * 32) >> 4), DESC_K + ((c * 16384 + kk * 32) >> 4));
        wg_commit();
      }
      bar_arrive(2 - w, 256);
      if (armer) {
        #pragma unroll
        for (int c = 0; c < 4; c++) mbar_expect(sBar + BAR_KF + 8 * c, 16384);
      }
      wg_wait<3>(); if (tid_in_wg == 0) mbar_arrive_cluster(remBar + BAR_KE);
      wg_wait<2>(); if (tid_in_wg == 32) mbar_arrive_cluster(remBar + BAR_KE);
      if (FIRST && t > 0 && w == 1) stage_half(oa, 0);
      wg_wait<1>(); if (tid_in_wg == 64) mbar_arrive_cluster(remBar + BAR_KE);
      wg_wait<0>(); if (tid_in_wg == 96) mbar_arrive_cluster(remBar + BAR_KE);
      if (!FIRST && j == 3 && tid_in_wg == 64) mbar_arrive(sBar + BAR_QE + 8 * w);

      if (t > 0 && (FIRST ? w == 0 : j == 1)) flush_half(FIRST ? 0 : 1);
      bool refresh;
      {
        int a0 = __vimax3_s32(__float_as_int(s[0]), __float_as_int(s[1]), __float_as_int(s[4]));
        int a1 = __vimax3_s32(__float_as_int(s[2]), __float_as_int(s[3]), __float_as_int(s[6]));
        int b0 = __vimax3_s32(__float_as_int(s[5]), __float_as_int(s[8]), __float_as_int(s[9]));
        int b1 = __vimax3_s32(__float_as_int(s[7]), __float_as_int(s[10]), __float_as_int(s[11]));
        #pragma unroll
        for (int i = 3; i < 15; i += 2) {
          a0 = __vimax3_s32(a0, __float_as_int(s[4 * i]), __float_as_int(s[4 * i + 1]));
          a1 = __vimax3_s32(a1, __float_as_int(s[4 * i + 2]), __float_as_int(s[4 * i + 3]));
          b0 = __vimax3_s32(b0, __float_as_int(s[4 * i + 4]), __float_as_int(s[4 * i + 5]));
          b1 = __vimax3_s32(b1, __float_as_int(s[4 * i + 6]), __float_as_int(s[4 * i + 7]));
        }
        a0 = __vimax3_s32(a0, __float_as_int(s[60]), __float_as_int(s[61]));
        a1 = __vimax3_s32(a1, __float_as_int(s[62]), __float_as_int(s[63]));
        a0 = max(a0, b0); a1 = max(a1, b1);
        if (FIRST) {
          a0 = max(a0, __shfl_xor_sync(0xffffffffu, a0, 1));
          a1 = max(a1, __shfl_xor_sync(0xffffffffu, a1, 1));
          a0 = max(a0, __shfl_xor_sync(0xffffffffu, a0, 2));
          a1 = max(a1, __shfl_xor_sync(0xffffffffu, a1, 2));
          m0 = __int_as_float(a0); m1 = __int_as_float(a1);
          th0 = __float_as_int(m0 + TAU_RAW); th1 = __float_as_int(m1 + TAU_RAW);
          l0 = 0.f; l1 = 0.f;
          refresh = __any_sync(0xffffffffu, (a0 | a1) < 0);
        } else {
          refresh = __any_sync(0xffffffffu, (a0 >= th0) || (a1 >= th1));
        }
      }
      if (refresh) {
        float x0 = fmaxf(s[0], s[1]), x1 = fmaxf(s[2], s[3]), y0 = fmaxf(s[4], s[5]), y1 = fmaxf(s[6], s[7]);
        #pragma unroll
        for (int i = 2; i < 16; i += 2) {
          x0 = fmaxf(x0, fmaxf(s[4 * i], s[4 * i + 1]));
          x1 = fmaxf(x1, fmaxf(s[4 * i + 2], s[4 * i + 3]));
          y0 = fmaxf(y0, fmaxf(s[4 * i + 4], s[4 * i + 5]));
          y1 = fmaxf(y1, fmaxf(s[4 * i + 6], s[4 * i + 7]));
        }
        x0 = fmaxf(x0, y0); x1 = fmaxf(x1, y1);
        x0 = fmaxf(x0, __shfl_xor_sync(0xffffffffu, x0, 1));
        x1 = fmaxf(x1, __shfl_xor_sync(0xffffffffu, x1, 1));
        x0 = fmaxf(x0, __shfl_xor_sync(0xffffffffu, x0, 2));
        x1 = fmaxf(x1, __shfl_xor_sync(0xffffffffu, x1, 2));
        if (!FIRST) {
          x0 = fmaxf(x0, m0); x1 = fmaxf(x1, m1);
          const float a0 = ex2((m0 - x0) * cs), a1 = ex2((m1 - x1) * cs);
          l0 *= a0; l1 *= a1;
          #pragma unroll
          for (int i = 0; i < 32; i++) {
            o[4 * i] *= a0; o[4 * i + 1] *= a0; o[4 * i + 2] *= a1; o[4 * i + 3] *= a1;
          }
        }
        m0 = x0; m1 = x1;
        const float t0 = x0 + TAU_RAW, t1 = x1 + TAU_RAW;
        th0 = t0 > 0.f ? __float_as_int(t0) : (int)0x80000000;
        th1 = t1 > 0.f ? __float_as_int(t1) : (int)0x80000000;
      }
      const float mc0 = -m0 * cs, mc1 = -m1 * cs;

      #pragma unroll
      for (int c = 0; c < 4; c++) {
        #pragma unroll
        for (int i = 4 * c; i < 4 * c + 4; i++) {
          const float e0 = ex2(fmaf(s[4 * i], cs, mc0)), e1 = ex2(fmaf(s[4 * i + 1], cs, mc0));
          const float e2 = ex2(fmaf(s[4 * i + 2], cs, mc1)), e3 = ex2(fmaf(s[4 * i + 3], cs, mc1));
          vadd(l0, e0); vadd(l1, e2); vadd(l0, e1); vadd(l1, e3);
          p[2 * i] = pack_bf16(e0, e1);
          p[2 * i + 1] = pack_bf16(e2, e3);
        }
        constexpr int C0 = FIRST ? 0 : 1;
        if (c < C0) continue;
        if (c == C0) {
          if (FIRST) {
            pack_half(ob, 1);
            if (t > 0 && w == 1) flush_half(0);
            #pragma unroll
            for (int i = 0; i < 128; i++) asm volatile("" : "=f"(o[i]));
          }
          rdy = mbar_test4(sBar + BAR_VF + (p[8 * C0 + 7] & zero), kvph);
          bar_sync(1 + w + (rdy & zero), 256);
        }
        #pragma unroll
        for (int cc = (c == C0 ? 0 : c); cc <= c; cc++) {
          if (!(rdy & (1 << cc))) mbar_wait(sBar + BAR_VF + 8 * cc, kvph);
          wg_fence();
          if (FIRST && cc == 0) wgmma_pv<0>(o, p[0], p[1], p[2], p[3], DESC_V);
          else wgmma_pv<1>(o, p[8 * cc], p[8 * cc + 1], p[8 * cc + 2], p[8 * cc + 3], DESC_V + ((cc * 16384) >> 4));
          wgmma_pv<1>(o, p[8 * cc + 4], p[8 * cc + 5], p[8 * cc + 6], p[8 * cc + 7], DESC_V + ((cc * 16384 + 2048) >> 4));
          wg_commit();
        }
      }
      bar_arrive(2 - w, 256);
      if (armer) {
        #pragma unroll
        for (int c = 0; c < 4; c++) mbar_expect(sBar + BAR_VF + 8 * c, 16384);
      }
      if (!FIRST && j == 3) {
        l0 += __shfl_xor_sync(0xffffffffu, l0, 1);
        l1 += __shfl_xor_sync(0xffffffffu, l1, 1);
        l0 += __shfl_xor_sync(0xffffffffu, l0, 2);
        l1 += __shfl_xor_sync(0xffffffffu, l1, 2);
        l0 = rcp(l0); inv1 = rcp(l1);
        orow_prev = qrow + w * 64 + wi * 16;
        qrow = __shfl_sync(0xffffffffu, qrow_of(t + 1), 0);
        staging_free();
      }
      wg_wait<3>(); if (tid_in_wg == 0) mbar_arrive_cluster(remBar + BAR_VE);
      wg_wait<2>(); if (tid_in_wg == 32) mbar_arrive_cluster(remBar + BAR_VE);
      if (FIRST && t > 0) { staging_free(); stage_half(ob, 0); }
      wg_wait<1>(); if (tid_in_wg == 64) mbar_arrive_cluster(remBar + BAR_VE);
      wg_wait<0>(); if (tid_in_wg == 96) mbar_arrive_cluster(remBar + BAR_VE);
      kvph ^= 1;
    };

    #pragma unroll
    for (int i = 0; i < 128; i++) o[i] = 0.f;
    #pragma unroll
    for (int i = 0; i < 32; i++) oa[i] = 0;
    for (int t = 0; qrow >= 0; t++) {
      block(TrueT{}, t, 0);
      #pragma unroll 1
      for (int j = 1; j < 4; j++) block(FalseT{}, t, j);
      qph ^= 1;
      rdy0 = mbar_test4(sBar + BAR_KF, kvph) & mbar_test4(sBar + BAR_QF + 32 * w, qph);
      pack_half(oa, 0);
      if (w == 0 || qrow < 0) stage_half(oa, 0);
    }
    {
      const uint32_t off2 = (OFF_Q + w * 32768 + wi * 4096) - (OFF_O + (w * 4 + wi) * 4096);
      uint32_t ob[32];
      pack_half(ob, 1);
      stage_half(ob, off2);
      asm volatile("fence.proxy.async.shared::cta;" ::: "memory");
      __syncwarp();
      if (lane == 0) {
        tma_store_3d(&tm.o, sO, orow_prev);
        tma_store_3d(&tm.o, sO + off2, orow_prev + 8);
        asm volatile("cp.async.bulk.commit_group;" ::: "memory");
      }
    }
    if (w == 0) bar_sync(1, 256);
    if (lane == 0) asm volatile("cp.async.bulk.wait_group.read 0;" ::: "memory");
    __syncwarp();
    cluster_arrive();
    cluster_wait();
  }
}

typedef CUresult (*EncodeFn)(CUtensorMap*, CUtensorMapDataType, cuuint32_t, void*, const cuuint64_t*, const cuuint64_t*,
                             const cuuint32_t*, const cuuint32_t*, CUtensorMapInterleave, CUtensorMapSwizzle,
                             CUtensorMapL2promotion, CUtensorMapFloatOOBfill);

void make_map(EncodeFn enc, CUtensorMap* tm, void* ptr, uint32_t rows, uint32_t chunks) {
  cuuint64_t dims[3] = {64, (cuuint64_t)NHEADS * SEQ, 4};
  cuuint64_t strides[2] = {HD * 2, 128};
  cuuint32_t box[3] = {64, rows, chunks};
  cuuint32_t es[3] = {1, 1, 1};
  enc(tm, CU_TENSOR_MAP_DATA_TYPE_BFLOAT16, 3, ptr, dims, strides, box, es, CU_TENSOR_MAP_INTERLEAVE_NONE,
      CU_TENSOR_MAP_SWIZZLE_128B, CU_TENSOR_MAP_L2_PROMOTION_L2_128B, CU_TENSOR_MAP_FLOAT_OOB_FILL_NONE);
}
void make_pf_map(EncodeFn enc, CUtensorMap* tm, void* ptr) {
  cuuint64_t dims[2] = {64, (cuuint64_t)NHEADS * SEQ * 4};
  cuuint64_t strides[1] = {128};
  cuuint32_t box[2] = {8, 128};
  cuuint32_t es[2] = {1, 1};
  enc(tm, CU_TENSOR_MAP_DATA_TYPE_BFLOAT16, 2, ptr, dims, strides, box, es, CU_TENSOR_MAP_INTERLEAVE_NONE,
      CU_TENSOR_MAP_SWIZZLE_NONE, CU_TENSOR_MAP_L2_PROMOTION_L2_128B, CU_TENSOR_MAP_FLOAT_OOB_FILL_NONE);
}

}

extern "C" void kernel_launch(void* const* d_in, const int* in_sizes, int n_in, void* d_out, int out_size) {
  static EncodeFn enc = nullptr;
  static int nA = 0, nB = 0;
  cudaLaunchConfig_t cfg = {};
  cfg.blockDim = dim3(NTHREADS); cfg.dynamicSmemBytes = SMEM_BYTES; cfg.stream = cudaStreamPerThread;
  cudaLaunchAttribute at[2];
  at[0].id = cudaLaunchAttributeClusterDimension;
  at[0].val.clusterDim.x = 4; at[0].val.clusterDim.y = 1; at[0].val.clusterDim.z = 1;
  at[1].id = cudaLaunchAttributeProgrammaticStreamSerialization;
  at[1].val.programmaticStreamSerializationAllowed = 1;
  cfg.attrs = at; cfg.numAttrs = 1;
  if (!enc) {
    void* fn = nullptr;
    cudaDriverEntryPointQueryResult st;
    cudaGetDriverEntryPoint("cuTensorMapEncodeTiled", &fn, cudaEnableDefault, &st);
    enc = (EncodeFn)fn;
    cudaFuncSetAttribute(mha_fwd_kernel<2>, cudaFuncAttributeMaxDynamicSharedMemorySize, SMEM_BYTES);
    cudaFuncSetAttribute(mha_fwd_kernel<4>, cudaFuncAttributeMaxDynamicSharedMemorySize, SMEM_BYTES);
    int dev = 0, sms = 0;
    cudaGetDevice(&dev);
    cudaDeviceGetAttribute(&sms, cudaDevAttrMultiProcessorCount, dev);
    cfg.gridDim = dim3(sms & ~3);
    if (cudaOccupancyMaxActiveClusters(&nA, mha_fwd_kernel<4>, &cfg) != cudaSuccess) { (void)cudaGetLastError(); nA = 0; }
    if (nA > sms / 4) nA = sms / 4;
    if (nA > NHEADS / 2) nA = NHEADS / 2;
    nB = (sms - 4 * nA) / 2;
    if (nB > NHEADS) nB = NHEADS;
  }
  Maps tm;
  make_map(enc, &tm.q, d_in[0], 64, 1);
  make_map(enc, &tm.k, d_in[1], 128, 1);
  make_map(enc, &tm.v, d_in[2], 32, 4);
  make_map(enc, &tm.o, d_out, 8, 4);
  make_pf_map(enc, &tm.pq, d_in[0]);
  make_pf_map(enc, &tm.pk, d_in[1]);
  make_pf_map(enc, &tm.pv, d_in[2]);

  int R = 1;
  while (nA * R + (nB * R) / 2 < NHEADS) R++;
  int hB = (nB * (R - 1)) / 2;
  if (hB < NHEADS - nA * R) hB = NHEADS - nA * R;
  if (hB > NHEADS - nA * (R - 1)) hB = NHEADS - nA * (R - 1);
  const int hA = NHEADS - hB;
  if (nA > 0) {
    cfg.gridDim = dim3(4 * nA);
    cudaLaunchKernelEx(&cfg, mha_fwd_kernel<4>, tm, 0, R - 1, 0, nA, nA * (R - 1), hA - nA * (R - 1));
    cfg.numAttrs = 2;
  }
  if (hB > 0) {
    const int nb = nB < 2 * hB ? nB : 2 * hB;
    at[0].val.clusterDim.x = 2;
    cfg.gridDim = dim3(2 * nb);
    cudaLaunchKernelEx(&cfg, mha_fwd_kernel<2>, tm, 2 * hA, 2 * hB / nb, 2 * hB % nb, nb, 0, 0);
  }
}
```

```cpp
#include <cuda_runtime.h>
#include <cuda_bf16.h>
#include <cuda.h>
#include <stdint.h>

namespace {

constexpr int SEQ = 512;
constexpr int HD = 256;
constexpr int NHEADS = 256;
constexpr int NTHREADS = 384;
constexpr int PF_DIST = 2;
constexpr int PF_INFLIGHT = 2;

constexpr uint32_t SMEM_BASE = 1024;
constexpr uint32_t OFF_Q = 0;
constexpr uint32_t OFF_K = 65536;
constexpr uint32_t OFF_V = 131072;
constexpr uint32_t OFF_O = 196608;
constexpr uint32_t OFF_BAR = 229376;
constexpr uint32_t SMEM_BYTES = OFF_BAR + 512 + 2048;
constexpr uint32_t W_PROG = 0, BAR_QE = 16, BAR_KF = 32, BAR_KE = 64, BAR_VF = 96, BAR_VE = 128,
                   BAR_QF = 160  , BAR_PF = 256, OFF_PFDST = 512;
constexpr uint32_t DESC_Q = ((SMEM_BASE + OFF_Q) >> 4) | (1u << 16);
constexpr uint32_t DESC_K = ((SMEM_BASE + OFF_K) >> 4) | (1u << 16);
constexpr uint32_t DESC_V = ((SMEM_BASE + OFF_V) >> 4) | ((4096u >> 4) << 16);

struct TrueT { static constexpr bool value = true; };
struct FalseT { static constexpr bool value = false; };

template <int SCALE_D>
__device__ __forceinline__ void wgmma_qk(float (&d)[64], uint32_t loA, uint32_t loB) {
  asm volatile("{\n.reg .b64 da, db;\nmov.b64 da, {%64, 0x40000040};\nmov.b64 db, {%65, 0x40000040};\n"
    "wgmma.mma_async.sync.aligned.m64n128k16.f32.bf16.bf16 {%0, %1, %2, %3, %4, %5, %6, %7, %8, %9, %10, %11, %12, %13, %14, %15, %16, %17, %18, %19, %20, %21, %22, %23, %24, %25, %26, %27, %28, %29, %30, %31, %32, %33, %34, %35, %36, %37, %38, %39, %40, %41, %42, %43, %44, %45, %46, %47, %48, %49, %50, %51, %52, %53, %54, %55, %56, %57, %58, %59, %60, %61, %62, %63}, da, db, %66, 1, 1, 0, 0;\n}\n"
    : "+f"(d[0]), "+f"(d[1]), "+f"(d[2]), "+f"(d[3]), "+f"(d[4]), "+f"(d[5]), "+f"(d[6]), "+f"(d[7]), "+f"(d[8]), "+f"(d[9]), "+f"(d[10]), "+f"(d[11]), "+f"(d[12]), "+f"(d[13]), "+f"(d[14]), "+f"(d[15]), "+f"(d[16]), "+f"(d[17]), "+f"(d[18]), "+f"(d[19]), "+f"(d[20]), "+f"(d[21]), "+f"(d[22]), "+f"(d[23]), "+f"(d[24]), "+f"(d[25]), "+f"(d[26]), "+f"(d[27]), "+f"(d[28]), "+f"(d[29]), "+f"(d[30]), "+f"(d[31]), "+f"(d[32]), "+f"(d[33]), "+f"(d[34]), "+f"(d[35]), "+f"(d[36]), "+f"(d[37]), "+f"(d[38]), "+f"(d[39]), "+f"(d[40]), "+f"(d[41]), "+f"(d[42]), "+f"(d[43]), "+f"(d[44]), "+f"(d[45]), "+f"(d[46]), "+f"(d[47]), "+f"(d[48]), "+f"(d[49]), "+f"(d[50]), "+f"(d[51]), "+f"(d[52]), "+f"(d[53]), "+f"(d[54]), "+f"(d[55]), "+f"(d[56]), "+f"(d[57]), "+f"(d[58]), "+f"(d[59]), "+f"(d[60]), "+f"(d[61]), "+f"(d[62]), "+f"(d[63])
    : "r"(loA), "r"(loB), "n"(SCALE_D));
}
template <int SCALE_D>
__device__ __forceinline__ void wgmma_pv(float (&d)[128], uint32_t a0, uint32_t a1, uint32_t a2, uint32_t a3, uint32_t loB) {
  asm volatile("{\n.reg .b64 db;\nmov.b64 db, {%132, 0x40000040};\n"
    "wgmma.mma_async.sync.aligned.m64n256k16.f32.bf16.bf16 {%0, %1, %2, %3, %4, %5, %6, %7, %8, %9, %10, %11, %12, %13, %14, %15, %16, %17, %18, %19, %20, %21, %22, %23, %24, %25, %26, %27, %28, %29, %30, %31, %32, %33, %34, %35, %36, %37, %38, %39, %40, %41, %42, %43, %44, %45, %46, %47, %48, %49, %50, %51, %52, %53, %54, %55, %56, %57, %58, %59, %60, %61, %62, %63, %64, %65, %66, %67, %68, %69, %70, %71, %72, %73, %74, %75, %76, %77, %78, %79, %80, %81, %82, %83, %84, %85, %86, %87, %88, %89, %90, %91, %92, %93, %94, %95, %96, %97, %98, %99, %100, %101, %102, %103, %104, %105, %106, %107, %108, %109, %110, %111, %112, %113, %114, %115, %116, %117, %118, %119, %120, %121, %122, %123, %124, %125, %126, %127}, {%128, %129, %130, %131}, db, %133, 1, 1, 1;\n}\n"
    : "+f"(d[0]), "+f"(d[1]), "+f"(d[2]), "+f"(d[3]), "+f"(d[4]), "+f"(d[5]), "+f"(d[6]), "+f"(d[7]), "+f"(d[8]), "+f"(d[9]), "+f"(d[10]), "+f"(d[11]), "+f"(d[12]), "+f"(d[13]), "+f"(d[14]), "+f"(d[15]), "+f"(d[16]), "+f"(d[17]), "+f"(d[18]), "+f"(d[19]), "+f"(d[20]), "+f"(d[21]), "+f"(d[22]), "+f"(d[23]), "+f"(d[24]), "+f"(d[25]), "+f"(d[26]), "+f"(d[27]), "+f"(d[28]), "+f"(d[29]), "+f"(d[30]), "+f"(d[31]), "+f"(d[32]), "+f"(d[33]), "+f"(d[34]), "+f"(d[35]), "+f"(d[36]), "+f"(d[37]), "+f"(d[38]), "+f"(d[39]), "+f"(d[40]), "+f"(d[41]), "+f"(d[42]), "+f"(d[43]), "+f"(d[44]), "+f"(d[45]), "+f"(d[46]), "+f"(d[47]), "+f"(d[48]), "+f"(d[49]), "+f"(d[50]), "+f"(d[51]), "+f"(d[52]), "+f"(d[53]), "+f"(d[54]), "+f"(d[55]), "+f"(d[56]), "+f"(d[57]), "+f"(d[58]), "+f"(d[59]), "+f"(d[60]), "+f"(d[61]), "+f"(d[62]), "+f"(d[63]), "+f"(d[64]), "+f"(d[65]), "+f"(d[66]), "+f"(d[67]), "+f"(d[68]), "+f"(d[69]), "+f"(d[70]), "+f"(d[71]), "+f"(d[72]), "+f"(d[73]), "+f"(d[74]), "+f"(d[75]), "+f"(d[76]), "+f"(d[77]), "+f"(d[78]), "+f"(d[79]), "+f"(d[80]), "+f"(d[81]), "+f"(d[82]), "+f"(d[83]), "+f"(d[84]), "+f"(d[85]), "+f"(d[86]), "+f"(d[87]), "+f"(d[88]), "+f"(d[89]), "+f"(d[90]), "+f"(d[91]), "+f"(d[92]), "+f"(d[93]), "+f"(d[94]), "+f"(d[95]), "+f"(d[96]), "+f"(d[97]), "+f"(d[98]), "+f"(d[99]), "+f"(d[100]), "+f"(d[101]), "+f"(d[102]), "+f"(d[103]), "+f"(d[104]), "+f"(d[105]), "+f"(d[106]), "+f"(d[107]), "+f"(d[108]), "+f"(d[109]), "+f"(d[110]), "+f"(d[111]), "+f"(d[112]), "+f"(d[113]), "+f"(d[114]), "+f"(d[115]), "+f"(d[116]), "+f"(d[117]), "+f"(d[118]), "+f"(d[119]), "+f"(d[120]), "+f"(d[121]), "+f"(d[122]), "+f"(d[123]), "+f"(d[124]), "+f"(d[125]), "+f"(d[126]), "+f"(d[127])
    : "r"(a0), "r"(a1), "r"(a2), "r"(a3), "r"(loB), "n"(SCALE_D));
}


__device__ __forceinline__ void wg_fence() { asm volatile("wgmma.fence.sync.aligned;" ::: "memory"); }
__device__ __forceinline__ void wg_commit() { asm volatile("wgmma.commit_group.sync.aligned;" ::: "memory"); }
template <int N> __device__ __forceinline__ void wg_wait() { asm volatile("wgmma.wait_group.sync.aligned %0;" :: "n"(N) : "memory"); }

__device__ __forceinline__ void mbar_init(uint32_t a, int c) { asm volatile("mbarrier.init.shared::cta.b64 [%0], %1;" :: "r"(a), "r"(c) : "memory"); }
__device__ __forceinline__ void mbar_expect(uint32_t a, int b) { asm volatile("mbarrier.arrive.expect_tx.shared::cta.b64 _, [%0], %1;" :: "r"(a), "r"(b) : "memory"); }
__device__ __forceinline__ void mbar_arrive(uint32_t a) { asm volatile("mbarrier.arrive.shared::cta.b64 _, [%0];" :: "r"(a) : "memory"); }
__device__ __forceinline__ void mbar_arrive_cluster(uint32_t a) { asm volatile("mbarrier.arrive.shared::cluster.b64 _, [%0];" :: "r"(a) : "memory"); }
__device__ __forceinline__ void mbar_wait(uint32_t a, uint32_t ph) {
  asm volatile("{\n.reg .pred p;\n.reg .u32 cnt;\nmov.u32 cnt, 0;\n"
               "LAB_WAIT:\nmbarrier.try_wait.parity.shared::cta.b64 p, [%0], %1;\n@p bra LAB_DONE;\n"
               "add.u32 cnt, cnt, 1;\nsetp.lt.u32 p, cnt, 4194304;\n@p bra LAB_WAIT;\ntrap;\nLAB_DONE:\n}\n"
               :: "r"(a), "r"(ph) : "memory");
}
__device__ __forceinline__ uint32_t mbar_test4(uint32_t a, uint32_t ph) {
  uint32_t m;
  asm volatile("{\n.reg .pred p, q, r, s;\n.reg .u32 x, y;\n"
               "mbarrier.test_wait.parity.shared::cta.b64 p, [%1], %2;\n"
               "mbarrier.test_wait.parity.shared::cta.b64 q, [%1+8], %2;\n"
               "mbarrier.test_wait.parity.shared::cta.b64 r, [%1+16], %2;\n"
               "mbarrier.test_wait.parity.shared::cta.b64 s, [%1+24], %2;\n"
               "selp.b32 x, 1, 0, p;\nselp.b32 y, 2, 0, q;\nor.b32 x, x, y;\nselp.b32 y, 4, 0, r;\nor.b32 x, x, y;\n"
               "selp.b32 y, 8, 0, s;\nor.b32 %0, x, y;\n}\n"
               : "=r"(m) : "r"(a), "r"(ph) : "memory");
  return m;
}
__device__ __forceinline__ void cluster_arrive() { asm volatile("barrier.cluster.arrive.relaxed.aligned;" ::: "memory"); }
__device__ __forceinline__ void cluster_wait() { asm volatile("barrier.cluster.wait.aligned;" ::: "memory"); }
__device__ __forceinline__ void bar_sync(int id, int n) { asm volatile("bar.sync %0, %1;" :: "r"(id), "r"(n) : "memory"); }
__device__ __forceinline__ void bar_arrive(int id, int n) { asm volatile("bar.arrive %0, %1;" :: "r"(id), "r"(n) : "memory"); }
__device__ __forceinline__ uint32_t mapa(uint32_t a, uint32_t cta) { uint32_t r; asm("mapa.shared::cluster.u32 %0, %1, %2;" : "=r"(r) : "r"(a), "r"(cta)); return r; }
__device__ __forceinline__ int lds_volatile(uint32_t a) { int v; asm volatile("ld.volatile.shared.u32 %0, [%1];" : "=r"(v) : "r"(a) : "memory"); return v; }
__device__ __forceinline__ bool elect_one() {
  uint32_t p;
  asm volatile("{\n.reg .pred P;\nelect.sync _|P, 0xffffffff;\nselp.b32 %0, 1, 0, P;\n}\n" : "=r"(p));
  return p != 0;
}

__device__ __forceinline__ void tma_load_3d(uint32_t dst, const CUtensorMap* tm, int c1, int c2, uint32_t bar, uint64_t pol) {
  asm volatile("cp.async.bulk.tensor.3d.shared::cluster.global.mbarrier::complete_tx::bytes.L2::cache_hint [%0], [%1, {%3, %4, %5}], [%2], %6;"
               :: "r"(dst), "l"(tm), "r"(bar), "r"(0), "r"(c1), "r"(c2), "l"(pol) : "memory");
}
__device__ __forceinline__ void tma_load_3d_mc(uint32_t dst, const CUtensorMap* tm, int c1, int c2, uint32_t bar, uint16_t mask, uint64_t pol) {
  asm volatile("cp.async.bulk.tensor.3d.shared::cluster.global.mbarrier::complete_tx::bytes.multicast::cluster.L2::cache_hint [%0], [%1, {%3, %4, %5}], [%2], %6, %7;"
               :: "r"(dst), "l"(tm), "r"(bar), "r"(0), "r"(c1), "r"(c2), "h"(mask), "l"(pol) : "memory");
}
__device__ __forceinline__ void tma_store_3d(const CUtensorMap* tm, uint32_t src, int c1) {
  asm volatile("cp.async.bulk.tensor.3d.global.shared::cta.bulk_group [%0, {%2, %3, %4}], [%1];"
               :: "l"(tm), "r"(src), "r"(0), "r"(c1), "r"(0) : "memory");
}
__device__ __forceinline__ float ex2(float x) { float y; asm volatile("ex2.approx.ftz.f32 %0, %1;" : "=f"(y) : "f"(x)); return y; }
__device__ __forceinline__ void vadd(float& a, float b) { asm volatile("add.f32 %0, %0, %1;" : "+f"(a) : "f"(b)); }
__device__ __forceinline__ float rcp(float x) { float y; asm("rcp.approx.ftz.f32 %0, %1;" : "=f"(y) : "f"(x)); return y; }
__device__ __forceinline__ uint32_t pack_bf16(float lo, float hi) { uint32_t r; asm volatile("cvt.rn.bf16x2.f32 %0, %1, %2;" : "=r"(r) : "f"(hi), "f"(lo)); return r; }
__device__ __forceinline__ void stmatrix_x4(uint32_t a, uint32_t r0, uint32_t r1, uint32_t r2, uint32_t r3) {
  asm volatile("stmatrix.sync.aligned.m8n8.x4.shared.b16 [%0], {%1, %2, %3, %4};" :: "r"(a), "r"(r0), "r"(r1), "r"(r2), "r"(r3) : "memory");
}

struct Maps { CUtensorMap q, k, v, o, pq, pk, pv; };

template <int CL>
__global__ void __launch_bounds__(NTHREADS, 1)
mha_fwd_kernel(const __grid_constant__ Maps tm, int unit0, int tiles_base, int tiles_rem, int nclusters) {
  extern __shared__ __align__(1024) char smem_raw[];
  const uint32_t sb = (uint32_t)__cvta_generic_to_shared(smem_raw);
  const uint32_t sBar = sb + OFF_BAR;
  const int tid = threadIdx.x;
  const int warp = __shfl_sync(0xffffffffu, tid >> 5, 0), lane = tid & 31;
  const int rank = blockIdx.x & (CL - 1);
  const int cluster_id = blockIdx.x / CL;
  if (CL == 4) asm volatile("griddepcontrol.launch_dependents;");
  const int ntiles = tiles_base + (cluster_id < tiles_rem ? 1 : 0);
  auto qrow_of = [&](int t) { return t < ntiles ? (unit0 + cluster_id + t * nclusters) * (128 * CL) + rank * 128 : -1; };
  const int qrow0 = (unit0 + cluster_id) * (128 * CL) + rank * 128;

  uint64_t pol_first;
  asm volatile("createpolicy.fractional.L2::evict_first.b64 %0, 1.0;" : "=l"(pol_first));
  if (tid == 64) {
    if ((sb & 0xFFFFFF) != SMEM_BASE) __trap();
    for (int i = 0; i < 8; i++) mbar_init(sBar + BAR_QF + 8 * i, 1);
    for (int i = 0; i < 2; i++) mbar_init(sBar + BAR_QE + 8 * i, 1);
    asm volatile("fence.mbarrier_init.release.cluster;" ::: "memory");
    asm volatile("fence.proxy.async.shared::cta;" ::: "memory");
    #pragma unroll
    for (int c = 0; c < 4; c++) {
      mbar_expect(sBar + BAR_QF + 8 * c, 8192);
      tma_load_3d(sb + OFF_Q + c * 8192, &tm.q, qrow0, c, sBar + BAR_QF + 8 * c, pol_first);
    }
  }
  if (tid == 96) {
    #pragma unroll
    for (int i = 0; i < 4 / CL; i++)
      asm volatile("cp.async.bulk.prefetch.tensor.3d.L2.global [%0, {%1, %2, %3}];"
                   :: "l"(&tm.k), "r"(0), "r"(qrow0 & ~(SEQ - 1)), "r"(i * CL + rank) : "memory");
  }
  if (tid == 0) {
    asm volatile("st.shared.u32 [%0], %1;" :: "r"(sBar + W_PROG), "r"(0) : "memory");
    for (int i = 0; i < 4; i++) {
      mbar_init(sBar + BAR_KF + 8 * i, 1); mbar_init(sBar + BAR_KE + 8 * i, 2 * CL);
      mbar_init(sBar + BAR_VF + 8 * i, 1); mbar_init(sBar + BAR_VE + 8 * i, 2 * CL);
    }
    for (int i = 0; i < PF_INFLIGHT; i++) mbar_init(sBar + BAR_PF + 8 * i, 1);
    for (int i = 0; i < 4; i++) { mbar_expect(sBar + BAR_KF + 8 * i, 16384); mbar_expect(sBar + BAR_VF + 8 * i, 16384); }
    asm volatile("fence.mbarrier_init.release.cluster;" ::: "memory");
  }
  if (tid == 32) {
    asm volatile("prefetch.tensormap [%0];" :: "l"(&tm.v) : "memory");
    asm volatile("prefetch.tensormap [%0];" :: "l"(&tm.o) : "memory");
  }
  cluster_arrive();
  cluster_wait();

  if (warp < 4) {
    asm volatile("setmaxnreg.dec.sync.aligned.u32 24;");
    if (warp < 2) {
      uint64_t pol = pol_first;
      if (CL == 2) asm volatile("createpolicy.fractional.L2::evict_unchanged.b64 %0, 1.0;" : "=l"(pol));
      const CUtensorMap* tmap = warp ? &tm.v : &tm.k;
      const uint32_t bE = sBar + (warp ? BAR_VE : BAR_KE), bF = sBar + (warp ? BAR_VF : BAR_KF);
      const uint32_t dst = sb + (warp ? OFF_V : OFF_K);
      uint32_t ph = 1;
      if (warp) mbar_wait(sBar + BAR_QF + 24, 0);
      for (int t = 0;; t++) {
        const int qrow = qrow_of(t);
        if (qrow < 0) break;
        const int row0 = qrow & ~(SEQ - 1);
        #pragma unroll 1
        for (int j = 0; j < 4; j++) {
          #pragma unroll
          for (int i = 0; i < 4 / CL; i++) {
            const int c = i * CL + rank;
            mbar_wait(bE + 8 * c, ph);
            if (elect_one()) {
              tma_load_3d_mc(dst + c * 16384, tmap, row0 + j * 128 + (warp ? c * 32 : 0), warp ? 0 : c, bF + 8 * c, (1 << CL) - 1, pol);
              if (warp && i == 0) asm volatile("st.volatile.shared.u32 [%0], %1;" :: "r"(sBar + W_PROG), "r"(t * 4 + j + 1) : "memory");
            }
          }
          ph ^= 1;
        }
      }
    } else if (warp == 2) {
      uint32_t ph = 1;
      mbar_wait(sBar + BAR_QF, 0);
      for (int t = 0;; t++) {
        const int qrow = qrow_of(t);
        if (qrow < 0) break;
        #pragma unroll 1
        for (int w = (t == 0 ? 1 : 0); w < 2; w++) {
          mbar_wait(sBar + BAR_QE + 8 * w, ph);
          if (elect_one()) {
            #pragma unroll
            for (int c = 0; c < 4; c++) {
              mbar_expect(sBar + BAR_QF + 32 * w + 8 * c, 8192);
              tma_load_3d(sb + OFF_Q + w * 32768 + c * 8192, &tm.q, qrow + w * 64, c, sBar + BAR_QF + 32 * w + 8 * c, pol_first);
            }
          }
        }
        ph ^= 1;
      }
    } else {
      uint32_t slot = 0, pph = 1;
      auto piece = [&](const CUtensorMap* tp, int line) {
        const uint32_t bar = sBar + BAR_PF + 8 * slot;
        mbar_wait(bar, pph);
        if (elect_one()) {
          mbar_expect(bar, 2048);
          asm volatile("cp.async.bulk.tensor.2d.shared::cluster.global.mbarrier::complete_tx::bytes [%0], [%1, {%3, %4}], [%2];"
                       :: "r"(sBar + OFF_PFDST), "l"(tp), "r"(bar), "r"(0), "r"(line) : "memory");
        }
        if (++slot == PF_INFLIGHT) { slot = 0; pph ^= 1; }
      };
      mbar_wait(sBar + BAR_QF + 56, 0);
      int qrow = qrow0;
      #pragma unroll 1
      for (int g = 1;; g++) {
        if ((g & 3) == 0) { qrow = qrow_of(g >> 2); if (qrow < 0) break; }
        int prog, it = 0;
        while ((prog = lds_volatile(sBar + W_PROG)) <= g - PF_DIST) {
          __nanosleep(100);
          if (++it > (1 << 24)) __trap();
        }
        if (prog > g) continue;
        const int kline = ((qrow & ~(SEQ - 1)) + (g & 3) * 128) * 4 + (qrow & (SEQ - 1));
        if ((g & 3) == 0) {
          piece(&tm.pq, qrow * 4); piece(&tm.pq, qrow * 4 + 128);
          piece(&tm.pk, kline);
          piece(&tm.pq, qrow * 4 + 256); piece(&tm.pq, qrow * 4 + 384);
        } else {
          piece(&tm.pk, kline);
        }
        piece(&tm.pv, kline);
      }
      #pragma unroll 1
      for (int i = 0; i < PF_INFLIGHT; i++) {
        mbar_wait(sBar + BAR_PF + 8 * slot, pph);
        if (++slot == PF_INFLIGHT) { slot = 0; pph ^= 1; }
      }
    }
    cluster_arrive();
    cluster_wait();
  } else {
    asm volatile("setmaxnreg.inc.sync.aligned.u32 240;");
    const int w = (warp >> 2) - 1;
    const int wi = warp & 3;
    const int tid_in_wg = tid & 127;
    constexpr float cs = 0.0625f * 1.4426950408889634f;
    constexpr float TAU_RAW = 8.0f / cs;
    const uint32_t remBar = mapa(sBar, wi & (CL - 1)) + 8 * wi;
    const bool armer = (w == 0) && (wi == 3) && (lane == 0);
    const uint32_t zero = (uint32_t)nclusters >> 30;
    const uint32_t descQ = DESC_Q + w * (32768 >> 4);
    const uint32_t sO = sb + OFF_O + (w * 4 + wi) * 4096;
    uint32_t sO_a = sO + (lane & 7) * 128 + (((lane >> 3) ^ (lane & 7)) << 4), sO_b = sO_a ^ 64;
    asm volatile("mov.b32 %0, %0;\nmov.b32 %1, %1;" : "+r"(sO_a), "+r"(sO_b));

    float o[128];
    float s[64];
    uint32_t p[32];
    uint32_t kvph = 0, qph = 0;
    float m0 = 0.f, m1 = 0.f, l0 = 0.f, l1 = 0.f;
    int th0 = 0, th1 = 0;
    int orow_prev = 0, qrow = qrow0;
    uint32_t rdy0 = 0;
    uint32_t oa[32];
    float inv1 = 0.f;
    if (w == 1) bar_arrive(1, 256);

    auto pack_half = [&](uint32_t (&r)[32], int h) {
      const float inv = h ? inv1 : l0;
      #pragma unroll
      for (int i = 0; i < 32; i++) r[i] = pack_bf16(o[4 * i + 2 * h] * inv, o[4 * i + 2 * h + 1] * inv);
    };
    auto staging_free = [&]() {
      if (lane == 0) asm volatile("cp.async.bulk.wait_group.read 0;" ::: "memory");
      __syncwarp();
    };
    auto stage_half = [&](const uint32_t (&r)[32], uint32_t off) {
      #pragma unroll
      for (int q = 0; q < 8; q++)
        stmatrix_x4(((q & 1) ? sO_b : sO_a) + off + (q >> 1) * 1024, r[4 * q], r[4 * q + 1], r[4 * q + 2], r[4 * q + 3]);
    };
    auto flush_half = [&](int h) {
      asm volatile("fence.proxy.async.shared::cta;" ::: "memory");
      __syncwarp();
      if (lane == 0) {
        tma_store_3d(&tm.o, sO, orow_prev + 8 * h);
        asm volatile("cp.async.bulk.commit_group;" ::: "memory");
      }
    };

    auto block = [&](auto first_tag, int t, int j) {
      constexpr bool FIRST = decltype(first_tag)::value;
      uint32_t ob[32];
      #pragma unroll
      for (int i = 0; i < 64; i++) asm volatile("" : "=f"(s[i]));
      uint32_t rdy = FIRST ? rdy0 : mbar_test4(sBar + BAR_KF, kvph);
      bar_sync(1 + w, 256);
      #pragma unroll
      for (int c = 0; c < 4; c++) {
        if (!(rdy & (1 << c))) {
          if (FIRST) mbar_wait(sBar + BAR_QF + 32 * w + 8 * c, qph);
          mbar_wait(sBar + BAR_KF + 8 * c, kvph);
        }
        wg_fence();
        if (c == 0) wgmma_qk<0>(s, descQ, DESC_K);
        else wgmma_qk<1>(s, descQ + ((c * 8192) >> 4), DESC_K + ((c * 16384) >> 4));
        #pragma unroll
        for (int kk = 1; kk < 4; kk++)
          wgmma_qk<1>(s, descQ + ((c * 8192 + kk * 32) >> 4), DESC_K + ((c * 16384 + kk * 32) >> 4));
        wg_commit();
      }
      bar_arrive(2 - w, 256);
      if (armer) {
        #pragma unroll
        for (int c = 0; c < 4; c++) mbar_expect(sBar + BAR_KF + 8 * c, 16384);
      }
      wg_wait<3>(); if (tid_in_wg == 0) mbar_arrive_cluster(remBar + BAR_KE);
      wg_wait<2>(); if (tid_in_wg == 32) mbar_arrive_cluster(remBar + BAR_KE);
      if (FIRST && t > 0 && w == 1) stage_half(oa, 0);
      wg_wait<1>(); if (tid_in_wg == 64) mbar_arrive_cluster(remBar + BAR_KE);
      wg_wait<0>(); if (tid_in_wg == 96) mbar_arrive_cluster(remBar + BAR_KE);
      if (!FIRST && j == 3 && tid_in_wg == 64) mbar_arrive(sBar + BAR_QE + 8 * w);

      if (t > 0 && (FIRST ? w == 0 : j == 1)) flush_half(FIRST ? 0 : 1);
      bool refresh;
      {
        int a0 = __vimax3_s32(__float_as_int(s[0]), __float_as_int(s[1]), __float_as_int(s[4]));
        int a1 = __vimax3_s32(__float_as_int(s[2]), __float_as_int(s[3]), __float_as_int(s[6]));
        int b0 = __vimax3_s32(__float_as_int(s[5]), __float_as_int(s[8]), __float_as_int(s[9]));
        int b1 = __vimax3_s32(__float_as_int(s[7]), __float_as_int(s[10]), __float_as_int(s[11]));
        #pragma unroll
        for (int i = 3; i < 15; i += 2) {
          a0 = __vimax3_s32(a0, __float_as_int(s[4 * i]), __float_as_int(s[4 * i + 1]));
          a1 = __vimax3_s32(a1, __float_as_int(s[4 * i + 2]), __float_as_int(s[4 * i + 3]));
          b0 = __vimax3_s32(b0, __float_as_int(s[4 * i + 4]), __float_as_int(s[4 * i + 5]));
          b1 = __vimax3_s32(b1, __float_as_int(s[4 * i + 6]), __float_as_int(s[4 * i + 7]));
        }
        a0 = __vimax3_s32(a0, __float_as_int(s[60]), __float_as_int(s[61]));
        a1 = __vimax3_s32(a1, __float_as_int(s[62]), __float_as_int(s[63]));
        a0 = max(a0, b0); a1 = max(a1, b1);
        if (FIRST) {
          a0 = max(a0, __shfl_xor_sync(0xffffffffu, a0, 1));
          a1 = max(a1, __shfl_xor_sync(0xffffffffu, a1, 1));
          a0 = max(a0, __shfl_xor_sync(0xffffffffu, a0, 2));
          a1 = max(a1, __shfl_xor_sync(0xffffffffu, a1, 2));
          m0 = __int_as_float(a0); m1 = __int_as_float(a1);
          th0 = __float_as_int(m0 + TAU_RAW); th1 = __float_as_int(m1 + TAU_RAW);
          l0 = 0.f; l1 = 0.f;
          refresh = __any_sync(0xffffffffu, (a0 | a1) < 0);
        } else {
          refresh = __any_sync(0xffffffffu, (a0 >= th0) || (a1 >= th1));
        }
      }
      if (refresh) {
        float x0 = fmaxf(s[0], s[1]), x1 = fmaxf(s[2], s[3]), y0 = fmaxf(s[4], s[5]), y1 = fmaxf(s[6], s[7]);
        #pragma unroll
        for (int i = 2; i < 16; i += 2) {
          x0 = fmaxf(x0, fmaxf(s[4 * i], s[4 * i + 1]));
          x1 = fmaxf(x1, fmaxf(s[4 * i + 2], s[4 * i + 3]));
          y0 = fmaxf(y0, fmaxf(s[4 * i + 4], s[4 * i + 5]));
          y1 = fmaxf(y1, fmaxf(s[4 * i + 6], s[4 * i + 7]));
        }
        x0 = fmaxf(x0, y0); x1 = fmaxf(x1, y1);
        x0 = fmaxf(x0, __shfl_xor_sync(0xffffffffu, x0, 1));
        x1 = fmaxf(x1, __shfl_xor_sync(0xffffffffu, x1, 1));
        x0 = fmaxf(x0, __shfl_xor_sync(0xffffffffu, x0, 2));
        x1 = fmaxf(x1, __shfl_xor_sync(0xffffffffu, x1, 2));
        if (!FIRST) {
          x0 = fmaxf(x0, m0); x1 = fmaxf(x1, m1);
          const float a0 = ex2((m0 - x0) * cs), a1 = ex2((m1 - x1) * cs);
          l0 *= a0; l1 *= a1;
          #pragma unroll
          for (int i = 0; i < 32; i++) {
            o[4 * i] *= a0; o[4 * i + 1] *= a0; o[4 * i + 2] *= a1; o[4 * i + 3] *= a1;
          }
        }
        m0 = x0; m1 = x1;
        const float t0 = x0 + TAU_RAW, t1 = x1 + TAU_RAW;
        th0 = t0 > 0.f ? __float_as_int(t0) : (int)0x80000000;
        th1 = t1 > 0.f ? __float_as_int(t1) : (int)0x80000000;
      }
      const float mc0 = -m0 * cs, mc1 = -m1 * cs;

      #pragma unroll
      for (int c = 0; c < 4; c++) {
        #pragma unroll
        for (int i = 4 * c; i < 4 * c + 4; i++) {
          const float e0 = ex2(fmaf(s[4 * i], cs, mc0)), e1 = ex2(fmaf(s[4 * i + 1], cs, mc0));
          const float e2 = ex2(fmaf(s[4 * i + 2], cs, mc1)), e3 = ex2(fmaf(s[4 * i + 3], cs, mc1));
          vadd(l0, e0); vadd(l1, e2); vadd(l0, e1); vadd(l1, e3);
          p[2 * i] = pack_bf16(e0, e1);
          p[2 * i + 1] = pack_bf16(e2, e3);
        }
        constexpr int C0 = FIRST ? 0 : 1;
        if (c < C0) continue;
        if (c == C0) {
          if (FIRST) {
            pack_half(ob, 1);
            if (t > 0 && w == 1) flush_half(0);
            #pragma unroll
            for (int i = 0; i < 128; i++) asm volatile("" : "=f"(o[i]));
          }
          rdy = mbar_test4(sBar + BAR_VF + (p[8 * C0 + 7] & zero), kvph);
          bar_sync(1 + w + (rdy & zero), 256);
        }
        #pragma unroll
        for (int cc = (c == C0 ? 0 : c); cc <= c; cc++) {
          if (!(rdy & (1 << cc))) mbar_wait(sBar + BAR_VF + 8 * cc, kvph);
          wg_fence();
          if (FIRST && cc == 0) wgmma_pv<0>(o, p[0], p[1], p[2], p[3], DESC_V);
          else wgmma_pv<1>(o, p[8 * cc], p[8 * cc + 1], p[8 * cc + 2], p[8 * cc + 3], DESC_V + ((cc * 16384) >> 4));
          wgmma_pv<1>(o, p[8 * cc + 4], p[8 * cc + 5], p[8 * cc + 6], p[8 * cc + 7], DESC_V + ((cc * 16384 + 2048) >> 4));
          wg_commit();
        }
      }
      bar_arrive(2 - w, 256);
      if (armer) {
        #pragma unroll
        for (int c = 0; c < 4; c++) mbar_expect(sBar + BAR_VF + 8 * c, 16384);
      }
      if (!FIRST && j == 3) {
        l0 += __shfl_xor_sync(0xffffffffu, l0, 1);
        l1 += __shfl_xor_sync(0xffffffffu, l1, 1);
        l0 += __shfl_xor_sync(0xffffffffu, l0, 2);
        l1 += __shfl_xor_sync(0xffffffffu, l1, 2);
        l0 = rcp(l0); inv1 = rcp(l1);
        orow_prev = qrow + w * 64 + wi * 16;
        qrow = qrow_of(t + 1);
        staging_free();
      }
      wg_wait<3>(); if (tid_in_wg == 0) mbar_arrive_cluster(remBar + BAR_VE);
      wg_wait<2>(); if (tid_in_wg == 32) mbar_arrive_cluster(remBar + BAR_VE);
      if (FIRST && t > 0) { staging_free(); stage_half(ob, 0); }
      wg_wait<1>(); if (tid_in_wg == 64) mbar_arrive_cluster(remBar + BAR_VE);
      wg_wait<0>(); if (tid_in_wg == 96) mbar_arrive_cluster(remBar + BAR_VE);
      kvph ^= 1;
    };

    #pragma unroll
    for (int i = 0; i < 128; i++) o[i] = 0.f;
    #pragma unroll
    for (int i = 0; i < 32; i++) oa[i] = 0;
    for (int t = 0; qrow >= 0; t++) {
      block(TrueT{}, t, 0);
      #pragma unroll 1
      for (int j = 1; j < 4; j++) block(FalseT{}, t, j);
      qph ^= 1;
      rdy0 = mbar_test4(sBar + BAR_KF, kvph) & mbar_test4(sBar + BAR_QF + 32 * w, qph);
      pack_half(oa, 0);
      if (w == 0 || qrow < 0) stage_half(oa, 0);
    }
    {
      const uint32_t off2 = (OFF_Q + w * 32768 + wi * 4096) - (OFF_O + (w * 4 + wi) * 4096);
      uint32_t ob[32];
      pack_half(ob, 1);
      stage_half(ob, off2);
      asm volatile("fence.proxy.async.shared::cta;" ::: "memory");
      __syncwarp();
      if (lane == 0) {
        tma_store_3d(&tm.o, sO, orow_prev);
        tma_store_3d(&tm.o, sO + off2, orow_prev + 8);
        asm volatile("cp.async.bulk.commit_group;" ::: "memory");
      }
    }
    if (w == 0) bar_sync(1, 256);
    if (lane == 0) asm volatile("cp.async.bulk.wait_group.read 0;" ::: "memory");
    __syncwarp();
    cluster_arrive();
    cluster_wait();
  }
}

typedef CUresult (*EncodeFn)(CUtensorMap*, CUtensorMapDataType, cuuint32_t, void*, const cuuint64_t*, const cuuint64_t*,
                             const cuuint32_t*, const cuuint32_t*, CUtensorMapInterleave, CUtensorMapSwizzle,
                             CUtensorMapL2promotion, CUtensorMapFloatOOBfill);

void make_map(EncodeFn enc, CUtensorMap* tm, void* ptr, uint32_t rows, uint32_t chunks) {
  cuuint64_t dims[3] = {64, (cuuint64_t)NHEADS * SEQ, 4};
  cuuint64_t strides[2] = {HD * 2, 128};
  cuuint32_t box[3] = {64, rows, chunks};
  cuuint32_t es[3] = {1, 1, 1};
  enc(tm, CU_TENSOR_MAP_DATA_TYPE_BFLOAT16, 3, ptr, dims, strides, box, es, CU_TENSOR_MAP_INTERLEAVE_NONE,
      CU_TENSOR_MAP_SWIZZLE_128B, CU_TENSOR_MAP_L2_PROMOTION_L2_128B, CU_TENSOR_MAP_FLOAT_OOB_FILL_NONE);
}
void make_pf_map(EncodeFn enc, CUtensorMap* tm, void* ptr) {
  cuuint64_t dims[2] = {64, (cuuint64_t)NHEADS * SEQ * 4};
  cuuint64_t strides[1] = {128};
  cuuint32_t box[2] = {8, 128};
  cuuint32_t es[2] = {1, 1};
  enc(tm, CU_TENSOR_MAP_DATA_TYPE_BFLOAT16, 2, ptr, dims, strides, box, es, CU_TENSOR_MAP_INTERLEAVE_NONE,
      CU_TENSOR_MAP_SWIZZLE_NONE, CU_TENSOR_MAP_L2_PROMOTION_L2_128B, CU_TENSOR_MAP_FLOAT_OOB_FILL_NONE);
}

}

extern "C" void kernel_launch(void* const* d_in, const int* in_sizes, int n_in, void* d_out, int out_size) {
  static EncodeFn enc = nullptr;
  static int nA = 0, nB = 0;
  cudaLaunchConfig_t cfg = {};
  cfg.blockDim = dim3(NTHREADS); cfg.dynamicSmemBytes = SMEM_BYTES; cfg.stream = cudaStreamPerThread;
  cudaLaunchAttribute at[2];
  at[0].id = cudaLaunchAttributeClusterDimension;
  at[0].val.clusterDim.x = 4; at[0].val.clusterDim.y = 1; at[0].val.clusterDim.z = 1;
  at[1].id = cudaLaunchAttributeProgrammaticStreamSerialization;
  at[1].val.programmaticStreamSerializationAllowed = 1;
  cfg.attrs = at; cfg.numAttrs = 1;
  if (!enc) {
    void* fn = nullptr;
    cudaDriverEntryPointQueryResult st;
    cudaGetDriverEntryPoint("cuTensorMapEncodeTiled", &fn, cudaEnableDefault, &st);
    enc = (EncodeFn)fn;
    cudaFuncSetAttribute(mha_fwd_kernel<2>, cudaFuncAttributeMaxDynamicSharedMemorySize, SMEM_BYTES);
    cudaFuncSetAttribute(mha_fwd_kernel<4>, cudaFuncAttributeMaxDynamicSharedMemorySize, SMEM_BYTES);
    int dev = 0, sms = 0;
    cudaGetDevice(&dev);
    cudaDeviceGetAttribute(&sms, cudaDevAttrMultiProcessorCount, dev);
    cfg.gridDim = dim3(sms & ~3);
    if (cudaOccupancyMaxActiveClusters(&nA, mha_fwd_kernel<4>, &cfg) != cudaSuccess) { (void)cudaGetLastError(); nA = 0; }
    if (nA > sms / 4) nA = sms / 4;
    if (nA > NHEADS / 2) nA = NHEADS / 2;
    nB = (sms - 4 * nA) / 2;
    if (nB > NHEADS) nB = NHEADS;
  }
  Maps tm;
  make_map(enc, &tm.q, d_in[0], 64, 1);
  make_map(enc, &tm.k, d_in[1], 128, 1);
  make_map(enc, &tm.v, d_in[2], 32, 4);
  make_map(enc, &tm.o, d_out, 8, 4);
  make_pf_map(enc, &tm.pq, d_in[0]);
  make_pf_map(enc, &tm.pk, d_in[1]);
  make_pf_map(enc, &tm.pv, d_in[2]);

  int R = 1;
  while (nA * R + (nB * R) / 2 < NHEADS) R++;
  const int hB = NHEADS - nA * R > 0 ? NHEADS - nA * R : 0;
  const int hA = NHEADS - hB;
  if (nA > 0) {
    cfg.gridDim = dim3(4 * nA);
    cudaLaunchKernelEx(&cfg, mha_fwd_kernel<4>, tm, 0, hA / nA, hA % nA, nA);
    cfg.numAttrs = 2;
  }
  if (hB > 0) {
    const int nb = nB < 2 * hB ? nB : 2 * hB;
    at[0].val.clusterDim.x = 2;
    cfg.gridDim = dim3(2 * nb);
    cudaLaunchKernelEx(&cfg, mha_fwd_kernel<2>, tm, 2 * hA, 2 * hB / nb, 2 * hB % nb, nb);
  }
}
```

```cpp
#include <cuda_runtime.h>
#include <cuda_bf16.h>
#include <cuda.h>
#include <stdint.h>

namespace {

constexpr int SEQ = 512;
constexpr int HD = 256;
constexpr int NHEADS = 256;
constexpr int NTHREADS = 384;
constexpr int PF_DIST = 2;
constexpr int PF_INFLIGHT = 2;

constexpr uint32_t SMEM_BASE = 1024;
constexpr uint32_t OFF_Q = 0;
constexpr uint32_t OFF_K = 65536;
constexpr uint32_t OFF_V = 131072;
constexpr uint32_t OFF_O = 196608;
constexpr uint32_t OFF_BAR = 229376;
constexpr uint32_t SMEM_BYTES = OFF_BAR + 512 + 2048;
constexpr uint32_t W_PROG = 0, BAR_QE = 16, BAR_KF = 32, BAR_KE = 64, BAR_VF = 96, BAR_VE = 128,
                   BAR_QF = 160  , BAR_PF = 256, OFF_PFDST = 512;
constexpr uint32_t DESC_Q = ((SMEM_BASE + OFF_Q) >> 4) | (1u << 16);
constexpr uint32_t DESC_K = ((SMEM_BASE + OFF_K) >> 4) | (1u << 16);
constexpr uint32_t DESC_V = ((SMEM_BASE + OFF_V) >> 4) | ((4096u >> 4) << 16);

struct TrueT { static constexpr bool value = true; };
struct FalseT { static constexpr bool value = false; };

template <int SCALE_D>
__device__ __forceinline__ void wgmma_qk(float (&d)[64], uint32_t loA, uint32_t loB) {
  asm volatile("{\n.reg .b64 da, db;\nmov.b64 da, {%64, 0x40000040};\nmov.b64 db, {%65, 0x40000040};\n"
    "wgmma.mma_async.sync.aligned.m64n128k16.f32.bf16.bf16 {%0, %1, %2, %3, %4, %5, %6, %7, %8, %9, %10, %11, %12, %13, %14, %15, %16, %17, %18, %19, %20, %21, %22, %23, %24, %25, %26, %27, %28, %29, %30, %31, %32, %33, %34, %35, %36, %37, %38, %39, %40, %41, %42, %43, %44, %45, %46, %47, %48, %49, %50, %51, %52, %53, %54, %55, %56, %57, %58, %59, %60, %61, %62, %63}, da, db, %66, 1, 1, 0, 0;\n}\n"
    : "+f"(d[0]), "+f"(d[1]), "+f"(d[2]), "+f"(d[3]), "+f"(d[4]), "+f"(d[5]), "+f"(d[6]), "+f"(d[7]), "+f"(d[8]), "+f"(d[9]), "+f"(d[10]), "+f"(d[11]), "+f"(d[12]), "+f"(d[13]), "+f"(d[14]), "+f"(d[15]), "+f"(d[16]), "+f"(d[17]), "+f"(d[18]), "+f"(d[19]), "+f"(d[20]), "+f"(d[21]), "+f"(d[22]), "+f"(d[23]), "+f"(d[24]), "+f"(d[25]), "+f"(d[26]), "+f"(d[27]), "+f"(d[28]), "+f"(d[29]), "+f"(d[30]), "+f"(d[31]), "+f"(d[32]), "+f"(d[33]), "+f"(d[34]), "+f"(d[35]), "+f"(d[36]), "+f"(d[37]), "+f"(d[38]), "+f"(d[39]), "+f"(d[40]), "+f"(d[41]), "+f"(d[42]), "+f"(d[43]), "+f"(d[44]), "+f"(d[45]), "+f"(d[46]), "+f"(d[47]), "+f"(d[48]), "+f"(d[49]), "+f"(d[50]), "+f"(d[51]), "+f"(d[52]), "+f"(d[53]), "+f"(d[54]), "+f"(d[55]), "+f"(d[56]), "+f"(d[57]), "+f"(d[58]), "+f"(d[59]), "+f"(d[60]), "+f"(d[61]), "+f"(d[62]), "+f"(d[63])
    : "r"(loA), "r"(loB), "n"(SCALE_D));
}
template <int SCALE_D>
__device__ __forceinline__ void wgmma_pv(float (&d)[128], uint32_t a0, uint32_t a1, uint32_t a2, uint32_t a3, uint32_t loB) {
  asm volatile("{\n.reg .b64 db;\nmov.b64 db, {%132, 0x40000040};\n"
    "wgmma.mma_async.sync.aligned.m64n256k16.f32.bf16.bf16 {%0, %1, %2, %3, %4, %5, %6, %7, %8, %9, %10, %11, %12, %13, %14, %15, %16, %17, %18, %19, %20, %21, %22, %23, %24, %25, %26, %27, %28, %29, %30, %31, %32, %33, %34, %35, %36, %37, %38, %39, %40, %41, %42, %43, %44, %45, %46, %47, %48, %49, %50, %51, %52, %53, %54, %55, %56, %57, %58, %59, %60, %61, %62, %63, %64, %65, %66, %67, %68, %69, %70, %71, %72, %73, %74, %75, %76, %77, %78, %79, %80, %81, %82, %83, %84, %85, %86, %87, %88, %89, %90, %91, %92, %93, %94, %95, %96, %97, %98, %99, %100, %101, %102, %103, %104, %105, %106, %107, %108, %109, %110, %111, %112, %113, %114, %115, %116, %117, %118, %119, %120, %121, %122, %123, %124, %125, %126, %127}, {%128, %129, %130, %131}, db, %133, 1, 1, 1;\n}\n"
    : "+f"(d[0]), "+f"(d[1]), "+f"(d[2]), "+f"(d[3]), "+f"(d[4]), "+f"(d[5]), "+f"(d[6]), "+f"(d[7]), "+f"(d[8]), "+f"(d[9]), "+f"(d[10]), "+f"(d[11]), "+f"(d[12]), "+f"(d[13]), "+f"(d[14]), "+f"(d[15]), "+f"(d[16]), "+f"(d[17]), "+f"(d[18]), "+f"(d[19]), "+f"(d[20]), "+f"(d[21]), "+f"(d[22]), "+f"(d[23]), "+f"(d[24]), "+f"(d[25]), "+f"(d[26]), "+f"(d[27]), "+f"(d[28]), "+f"(d[29]), "+f"(d[30]), "+f"(d[31]), "+f"(d[32]), "+f"(d[33]), "+f"(d[34]), "+f"(d[35]), "+f"(d[36]), "+f"(d[37]), "+f"(d[38]), "+f"(d[39]), "+f"(d[40]), "+f"(d[41]), "+f"(d[42]), "+f"(d[43]), "+f"(d[44]), "+f"(d[45]), "+f"(d[46]), "+f"(d[47]), "+f"(d[48]), "+f"(d[49]), "+f"(d[50]), "+f"(d[51]), "+f"(d[52]), "+f"(d[53]), "+f"(d[54]), "+f"(d[55]), "+f"(d[56]), "+f"(d[57]), "+f"(d[58]), "+f"(d[59]), "+f"(d[60]), "+f"(d[61]), "+f"(d[62]), "+f"(d[63]), "+f"(d[64]), "+f"(d[65]), "+f"(d[66]), "+f"(d[67]), "+f"(d[68]), "+f"(d[69]), "+f"(d[70]), "+f"(d[71]), "+f"(d[72]), "+f"(d[73]), "+f"(d[74]), "+f"(d[75]), "+f"(d[76]), "+f"(d[77]), "+f"(d[78]), "+f"(d[79]), "+f"(d[80]), "+f"(d[81]), "+f"(d[82]), "+f"(d[83]), "+f"(d[84]), "+f"(d[85]), "+f"(d[86]), "+f"(d[87]), "+f"(d[88]), "+f"(d[89]), "+f"(d[90]), "+f"(d[91]), "+f"(d[92]), "+f"(d[93]), "+f"(d[94]), "+f"(d[95]), "+f"(d[96]), "+f"(d[97]), "+f"(d[98]), "+f"(d[99]), "+f"(d[100]), "+f"(d[101]), "+f"(d[102]), "+f"(d[103]), "+f"(d[104]), "+f"(d[105]), "+f"(d[106]), "+f"(d[107]), "+f"(d[108]), "+f"(d[109]), "+f"(d[110]), "+f"(d[111]), "+f"(d[112]), "+f"(d[113]), "+f"(d[114]), "+f"(d[115]), "+f"(d[116]), "+f"(d[117]), "+f"(d[118]), "+f"(d[119]), "+f"(d[120]), "+f"(d[121]), "+f"(d[122]), "+f"(d[123]), "+f"(d[124]), "+f"(d[125]), "+f"(d[126]), "+f"(d[127])
    : "r"(a0), "r"(a1), "r"(a2), "r"(a3), "r"(loB), "n"(SCALE_D));
}


__device__ __forceinline__ void wg_fence() { asm volatile("wgmma.fence.sync.aligned;" ::: "memory"); }
__device__ __forceinline__ void wg_commit() { asm volatile("wgmma.commit_group.sync.aligned;" ::: "memory"); }
template <int N> __device__ __forceinline__ void wg_wait() { asm volatile("wgmma.wait_group.sync.aligned %0;" :: "n"(N) : "memory"); }

__device__ __forceinline__ void mbar_init(uint32_t a, int c) { asm volatile("mbarrier.init.shared::cta.b64 [%0], %1;" :: "r"(a), "r"(c) : "memory"); }
__device__ __forceinline__ void mbar_expect(uint32_t a, int b) { asm volatile("mbarrier.arrive.expect_tx.shared::cta.b64 _, [%0], %1;" :: "r"(a), "r"(b) : "memory"); }
__device__ __forceinline__ void mbar_arrive(uint32_t a) { asm volatile("mbarrier.arrive.shared::cta.b64 _, [%0];" :: "r"(a) : "memory"); }
__device__ __forceinline__ void mbar_arrive_cluster(uint32_t a) { asm volatile("mbarrier.arrive.shared::cluster.b64 _, [%0];" :: "r"(a) : "memory"); }
__device__ __forceinline__ void mbar_wait(uint32_t a, uint32_t ph) {
  asm volatile("{\n.reg .pred p;\n.reg .u32 cnt;\nmov.u32 cnt, 0;\n"
               "LAB_WAIT:\nmbarrier.try_wait.parity.shared::cta.b64 p, [%0], %1;\n@p bra LAB_DONE;\n"
               "add.u32 cnt, cnt, 1;\nsetp.lt.u32 p, cnt, 4194304;\n@p bra LAB_WAIT;\ntrap;\nLAB_DONE:\n}\n"
               :: "r"(a), "r"(ph) : "memory");
}
__device__ __forceinline__ uint32_t mbar_test4(uint32_t a, uint32_t ph) {
  uint32_t m;
  asm volatile("{\n.reg .pred p, q, r, s;\n.reg .u32 x, y;\n"
               "mbarrier.test_wait.parity.shared::cta.b64 p, [%1], %2;\n"
               "mbarrier.test_wait.parity.shared::cta.b64 q, [%1+8], %2;\n"
               "mbarrier.test_wait.parity.shared::cta.b64 r, [%1+16], %2;\n"
               "mbarrier.test_wait.parity.shared::cta.b64 s, [%1+24], %2;\n"
               "selp.b32 x, 1, 0, p;\nselp.b32 y, 2, 0, q;\nor.b32 x, x, y;\nselp.b32 y, 4, 0, r;\nor.b32 x, x, y;\n"
               "selp.b32 y, 8, 0, s;\nor.b32 %0, x, y;\n}\n"
               : "=r"(m) : "r"(a), "r"(ph) : "memory");
  return m;
}
__device__ __forceinline__ void cluster_arrive() { asm volatile("barrier.cluster.arrive.relaxed.aligned;" ::: "memory"); }
__device__ __forceinline__ void cluster_wait() { asm volatile("barrier.cluster.wait.aligned;" ::: "memory"); }
__device__ __forceinline__ void bar_sync(int id, int n) { asm volatile("bar.sync %0, %1;" :: "r"(id), "r"(n) : "memory"); }
__device__ __forceinline__ void bar_arrive(int id, int n) { asm volatile("bar.arrive %0, %1;" :: "r"(id), "r"(n) : "memory"); }
__device__ __forceinline__ uint32_t mapa(uint32_t a, uint32_t cta) { uint32_t r; asm("mapa.shared::cluster.u32 %0, %1, %2;" : "=r"(r) : "r"(a), "r"(cta)); return r; }
__device__ __forceinline__ int lds_volatile(uint32_t a) { int v; asm volatile("ld.volatile.shared.u32 %0, [%1];" : "=r"(v) : "r"(a) : "memory"); return v; }
__device__ __forceinline__ bool elect_one() {
  uint32_t p;
  asm volatile("{\n.reg .pred P;\nelect.sync _|P, 0xffffffff;\nselp.b32 %0, 1, 0, P;\n}\n" : "=r"(p));
  return p != 0;
}

__device__ __forceinline__ void tma_load_3d(uint32_t dst, const CUtensorMap* tm, int c1, int c2, uint32_t bar, uint64_t pol) {
  asm volatile("cp.async.bulk.tensor.3d.shared::cluster.global.mbarrier::complete_tx::bytes.L2::cache_hint [%0], [%1, {%3, %4, %5}], [%2], %6;"
               :: "r"(dst), "l"(tm), "r"(bar), "r"(0), "r"(c1), "r"(c2), "l"(pol) : "memory");
}
__device__ __forceinline__ void tma_load_3d_mc(uint32_t dst, const CUtensorMap* tm, int c1, int c2, uint32_t bar, uint16_t mask, uint64_t pol) {
  asm volatile("cp.async.bulk.tensor.3d.shared::cluster.global.mbarrier::complete_tx::bytes.multicast::cluster.L2::cache_hint [%0], [%1, {%3, %4, %5}], [%2], %6, %7;"
               :: "r"(dst), "l"(tm), "r"(bar), "r"(0), "r"(c1), "r"(c2), "h"(mask), "l"(pol) : "memory");
}
__device__ __forceinline__ void tma_store_3d(const CUtensorMap* tm, uint32_t src, int c1) {
  asm volatile("cp.async.bulk.tensor.3d.global.shared::cta.bulk_group [%0, {%2, %3, %4}], [%1];"
               :: "l"(tm), "r"(src), "r"(0), "r"(c1), "r"(0) : "memory");
}
__device__ __forceinline__ float ex2(float x) { float y; asm volatile("ex2.approx.ftz.f32 %0, %1;" : "=f"(y) : "f"(x)); return y; }
__device__ __forceinline__ void vadd(float& a, float b) { asm volatile("add.f32 %0, %0, %1;" : "+f"(a) : "f"(b)); }
__device__ __forceinline__ void vmul(float& a, float b) { asm volatile("mul.f32 %0, %0, %1;" : "+f"(a) : "f"(b)); }
__device__ __forceinline__ float rcp(float x) { float y; asm("rcp.approx.ftz.f32 %0, %1;" : "=f"(y) : "f"(x)); return y; }
__device__ __forceinline__ uint32_t pack_bf16(float lo, float hi) { uint32_t r; asm volatile("cvt.rn.bf16x2.f32 %0, %1, %2;" : "=r"(r) : "f"(hi), "f"(lo)); return r; }
__device__ __forceinline__ void stmatrix_x4(uint32_t a, uint32_t r0, uint32_t r1, uint32_t r2, uint32_t r3) {
  asm volatile("stmatrix.sync.aligned.m8n8.x4.shared.b16 [%0], {%1, %2, %3, %4};" :: "r"(a), "r"(r0), "r"(r1), "r"(r2), "r"(r3) : "memory");
}

struct Maps { CUtensorMap q, k, v, o, pq, pk, pv; };

template <int CL>
__global__ void __launch_bounds__(NTHREADS, 1)
mha_fwd_kernel(const __grid_constant__ Maps tm, int unit0, int tiles_base, int tiles_rem, int nclusters) {
  extern __shared__ __align__(1024) char smem_raw[];
  const uint32_t sb = (uint32_t)__cvta_generic_to_shared(smem_raw);
  const uint32_t sBar = sb + OFF_BAR;
  const int tid = threadIdx.x;
  const int warp = __shfl_sync(0xffffffffu, tid >> 5, 0), lane = tid & 31;
  const int rank = blockIdx.x & (CL - 1);
  const int cluster_id = blockIdx.x / CL;
  if (CL == 4) asm volatile("griddepcontrol.launch_dependents;");
  const int ntiles = tiles_base + (cluster_id < tiles_rem ? 1 : 0);
  auto qrow_of = [&](int t) { return t < ntiles ? (unit0 + cluster_id + t * nclusters) * (128 * CL) + rank * 128 : -1; };
  const int qrow0 = (unit0 + cluster_id) * (128 * CL) + rank * 128;

  uint64_t pol_first;
  asm volatile("createpolicy.fractional.L2::evict_first.b64 %0, 1.0;" : "=l"(pol_first));
  if (tid == 64) {
    if ((sb & 0xFFFFFF) != SMEM_BASE) __trap();
    for (int i = 0; i < 8; i++) mbar_init(sBar + BAR_QF + 8 * i, 1);
    for (int i = 0; i < 2; i++) mbar_init(sBar + BAR_QE + 8 * i, 1);
    asm volatile("fence.mbarrier_init.release.cluster;" ::: "memory");
    asm volatile("fence.proxy.async.shared::cta;" ::: "memory");
    #pragma unroll
    for (int c = 0; c < 4; c++) {
      mbar_expect(sBar + BAR_QF + 8 * c, 8192);
      tma_load_3d(sb + OFF_Q + c * 8192, &tm.q, qrow0, c, sBar + BAR_QF + 8 * c, pol_first);
    }
  }
  if (tid == 96) {
    #pragma unroll
    for (int i = 0; i < 4 / CL; i++)
      asm volatile("cp.async.bulk.prefetch.tensor.3d.L2.global [%0, {%1, %2, %3}];"
                   :: "l"(&tm.k), "r"(0), "r"(qrow0 & ~(SEQ - 1)), "r"(i * CL + rank) : "memory");
  }
  if (tid == 0) {
    asm volatile("st.shared.u32 [%0], %1;" :: "r"(sBar + W_PROG), "r"(0) : "memory");
    for (int i = 0; i < 4; i++) {
      mbar_init(sBar + BAR_KF + 8 * i, 1); mbar_init(sBar + BAR_KE + 8 * i, 2 * CL);
      mbar_init(sBar + BAR_VF + 8 * i, 1); mbar_init(sBar + BAR_VE + 8 * i, 2 * CL);
    }
    for (int i = 0; i < PF_INFLIGHT; i++) mbar_init(sBar + BAR_PF + 8 * i, 1);
    for (int i = 0; i < 4; i++) { mbar_expect(sBar + BAR_KF + 8 * i, 16384); mbar_expect(sBar + BAR_VF + 8 * i, 16384); }
    asm volatile("fence.mbarrier_init.release.cluster;" ::: "memory");
  }
  if (tid == 32) {
    asm volatile("prefetch.tensormap [%0];" :: "l"(&tm.v) : "memory");
    asm volatile("prefetch.tensormap [%0];" :: "l"(&tm.o) : "memory");
  }
  cluster_arrive();
  cluster_wait();

  if (warp < 4) {
    asm volatile("setmaxnreg.dec.sync.aligned.u32 24;");
    if (warp < 2) {
      uint64_t pol = pol_first;
      if (CL == 2) asm volatile("createpolicy.fractional.L2::evict_normal.b64 %0, 1.0;" : "=l"(pol));
      const CUtensorMap* tmap = warp ? &tm.v : &tm.k;
      const uint32_t bE = sBar + (warp ? BAR_VE : BAR_KE), bF = sBar + (warp ? BAR_VF : BAR_KF);
      const uint32_t dst = sb + (warp ? OFF_V : OFF_K);
      uint32_t ph = 1;
      if (warp) mbar_wait(sBar + BAR_QF + 24, 0);
      for (int t = 0;; t++) {
        const int qrow = qrow_of(t);
        if (qrow < 0) break;
        const int row0 = qrow & ~(SEQ - 1);
        #pragma unroll 1
        for (int j = 0; j < 4; j++) {
          #pragma unroll
          for (int i = 0; i < 4 / CL; i++) {
            const int c = i * CL + rank;
            mbar_wait(bE + 8 * c, ph);
            if (elect_one()) {
              tma_load_3d_mc(dst + c * 16384, tmap, row0 + j * 128 + (warp ? c * 32 : 0), warp ? 0 : c, bF + 8 * c, (1 << CL) - 1, pol);
              if (warp && i == 0) asm volatile("st.volatile.shared.u32 [%0], %1;" :: "r"(sBar + W_PROG), "r"(t * 4 + j + 1) : "memory");
            }
          }
          ph ^= 1;
        }
      }
    } else if (warp == 2) {
      uint32_t ph = 1;
      mbar_wait(sBar + BAR_QF, 0);
      for (int t = 0;; t++) {
        const int qrow = qrow_of(t);
        if (qrow < 0) break;
        #pragma unroll 1
        for (int w = (t == 0 ? 1 : 0); w < 2; w++) {
          mbar_wait(sBar + BAR_QE + 8 * w, ph);
          if (elect_one()) {
            #pragma unroll
            for (int c = 0; c < 4; c++) {
              mbar_expect(sBar + BAR_QF + 32 * w + 8 * c, 8192);
              tma_load_3d(sb + OFF_Q + w * 32768 + c * 8192, &tm.q, qrow + w * 64, c, sBar + BAR_QF + 32 * w + 8 * c, pol_first);
            }
          }
        }
        ph ^= 1;
      }
    } else {
      uint32_t slot = 0, pph = 1;
      auto piece = [&](const CUtensorMap* tp, int line) {
        const uint32_t bar = sBar + BAR_PF + 8 * slot;
        mbar_wait(bar, pph);
        if (elect_one()) {
          mbar_expect(bar, 2048);
          asm volatile("cp.async.bulk.tensor.2d.shared::cluster.global.mbarrier::complete_tx::bytes [%0], [%1, {%3, %4}], [%2];"
                       :: "r"(sBar + OFF_PFDST), "l"(tp), "r"(bar), "r"(0), "r"(line) : "memory");
        }
        if (++slot == PF_INFLIGHT) { slot = 0; pph ^= 1; }
      };
      mbar_wait(sBar + BAR_QF + 56, 0);
      int qrow = qrow0;
      #pragma unroll 1
      for (int g = 1;; g++) {
        if ((g & 3) == 0) { qrow = qrow_of(g >> 2); if (qrow < 0) break; }
        int prog, it = 0;
        while ((prog = lds_volatile(sBar + W_PROG)) <= g - PF_DIST) {
          __nanosleep(100);
          if (++it > (1 << 24)) __trap();
        }
        if (prog > g) continue;
        const int kline = ((qrow & ~(SEQ - 1)) + (g & 3) * 128) * 4 + (qrow & (SEQ - 1));
        if ((g & 3) == 0) {
          piece(&tm.pq, qrow * 4); piece(&tm.pq, qrow * 4 + 128);
          piece(&tm.pk, kline);
          piece(&tm.pq, qrow * 4 + 256); piece(&tm.pq, qrow * 4 + 384);
        } else {
          piece(&tm.pk, kline);
        }
        piece(&tm.pv, kline);
      }
      #pragma unroll 1
      for (int i = 0; i < PF_INFLIGHT; i++) {
        mbar_wait(sBar + BAR_PF + 8 * slot, pph);
        if (++slot == PF_INFLIGHT) { slot = 0; pph ^= 1; }
      }
    }
    cluster_arrive();
    cluster_wait();
  } else {
    asm volatile("setmaxnreg.inc.sync.aligned.u32 240;");
    const int w = (warp >> 2) - 1;
    const int wi = warp & 3;
    const int tid_in_wg = tid & 127;
    constexpr float cs = 0.0625f * 1.4426950408889634f;
    constexpr float TAU_RAW = 8.0f / cs;
    const uint32_t remBar = mapa(sBar, wi & (CL - 1)) + 8 * wi;
    const bool armer = (w == 0) && (wi == 3) && (lane == 0);
    const uint32_t zero = (uint32_t)nclusters >> 30;
    const uint32_t descQ = DESC_Q + w * (32768 >> 4);
    const uint32_t sO = sb + OFF_O + (w * 4 + wi) * 4096;
    uint32_t sO_a = sO + (lane & 7) * 128 + (((lane >> 3) ^ (lane & 7)) << 4), sO_b = sO_a ^ 64;
    asm volatile("mov.b32 %0, %0;\nmov.b32 %1, %1;" : "+r"(sO_a), "+r"(sO_b));

    float o[128];
    float s[64];
    uint32_t p[32];
    uint32_t kvph = 0, qph = 0;
    float m0 = 0.f, m1 = 0.f, l0 = 0.f, l1 = 0.f;
    int th0 = 0, th1 = 0;
    int orow_prev = 0, qrow = qrow0;
    uint32_t rdy0 = 0;
    uint32_t oa[32];
    if (w == 1) bar_arrive(1, 256);

    auto pack_half1 = [&](uint32_t (&r)[32]) {
      #pragma unroll
      for (int i = 0; i < 32; i++) r[i] = pack_bf16(o[4 * i + 2], o[4 * i + 3]);
    };
    auto staging_free = [&]() {
      if (lane == 0) asm volatile("cp.async.bulk.wait_group.read 0;" ::: "memory");
      __syncwarp();
    };
    auto stage_half = [&](const uint32_t (&r)[32], uint32_t off) {
      #pragma unroll
      for (int q = 0; q < 8; q++)
        stmatrix_x4(((q & 1) ? sO_b : sO_a) + off + (q >> 1) * 1024, r[4 * q], r[4 * q + 1], r[4 * q + 2], r[4 * q + 3]);
    };
    auto flush_half = [&](int h) {
      asm volatile("fence.proxy.async.shared::cta;" ::: "memory");
      __syncwarp();
      if (lane == 0) {
        tma_store_3d(&tm.o, sO, orow_prev + 8 * h);
        asm volatile("cp.async.bulk.commit_group;" ::: "memory");
      }
    };

    auto block = [&](auto first_tag, int t, int j) {
      constexpr bool FIRST = decltype(first_tag)::value;
      uint32_t ob[32];
      #pragma unroll
      for (int i = 0; i < 64; i++) asm volatile("" : "=f"(s[i]));
      uint32_t rdy = FIRST ? rdy0 : mbar_test4(sBar + BAR_KF, kvph);
      bar_sync(1 + w, 256);
      #pragma unroll
      for (int c = 0; c < 4; c++) {
        if (!(rdy & (1 << c))) {
          if (FIRST) mbar_wait(sBar + BAR_QF + 32 * w + 8 * c, qph);
          mbar_wait(sBar + BAR_KF + 8 * c, kvph);
        }
        wg_fence();
        if (c == 0) wgmma_qk<0>(s, descQ, DESC_K);
        else wgmma_qk<1>(s, descQ + ((c * 8192) >> 4), DESC_K + ((c * 16384) >> 4));
        #pragma unroll
        for (int kk = 1; kk < 4; kk++)
          wgmma_qk<1>(s, descQ + ((c * 8192 + kk * 32) >> 4), DESC_K + ((c * 16384 + kk * 32) >> 4));
        wg_commit();
      }
      bar_arrive(2 - w, 256);
      if (armer) {
        #pragma unroll
        for (int c = 0; c < 4; c++) mbar_expect(sBar + BAR_KF + 8 * c, 16384);
      }
      wg_wait<3>(); if (tid_in_wg == 0) mbar_arrive_cluster(remBar + BAR_KE);
      wg_wait<2>(); if (tid_in_wg == 32) mbar_arrive_cluster(remBar + BAR_KE);
      if (FIRST && t > 0 && w == 1) stage_half(oa, 0);
      wg_wait<1>(); if (tid_in_wg == 64) mbar_arrive_cluster(remBar + BAR_KE);
      wg_wait<0>(); if (tid_in_wg == 96) mbar_arrive_cluster(remBar + BAR_KE);
      if (!FIRST && j == 3 && tid_in_wg == 64) mbar_arrive(sBar + BAR_QE + 8 * w);

      if (t > 0 && (FIRST ? w == 0 : j == 1)) flush_half(FIRST ? 0 : 1);
      bool refresh;
      {
        int a0 = __vimax3_s32(__float_as_int(s[0]), __float_as_int(s[1]), __float_as_int(s[4]));
        int a1 = __vimax3_s32(__float_as_int(s[2]), __float_as_int(s[3]), __float_as_int(s[6]));
        int b0 = __vimax3_s32(__float_as_int(s[5]), __float_as_int(s[8]), __float_as_int(s[9]));
        int b1 = __vimax3_s32(__float_as_int(s[7]), __float_as_int(s[10]), __float_as_int(s[11]));
        #pragma unroll
        for (int i = 3; i < 15; i += 2) {
          a0 = __vimax3_s32(a0, __float_as_int(s[4 * i]), __float_as_int(s[4 * i + 1]));
          a1 = __vimax3_s32(a1, __float_as_int(s[4 * i + 2]), __float_as_int(s[4 * i + 3]));
          b0 = __vimax3_s32(b0, __float_as_int(s[4 * i + 4]), __float_as_int(s[4 * i + 5]));
          b1 = __vimax3_s32(b1, __float_as_int(s[4 * i + 6]), __float_as_int(s[4 * i + 7]));
        }
        a0 = __vimax3_s32(a0, __float_as_int(s[60]), __float_as_int(s[61]));
        a1 = __vimax3_s32(a1, __float_as_int(s[62]), __float_as_int(s[63]));
        a0 = max(a0, b0); a1 = max(a1, b1);
        if (FIRST) {
          a0 = max(a0, __shfl_xor_sync(0xffffffffu, a0, 1));
          a1 = max(a1, __shfl_xor_sync(0xffffffffu, a1, 1));
          a0 = max(a0, __shfl_xor_sync(0xffffffffu, a0, 2));
          a1 = max(a1, __shfl_xor_sync(0xffffffffu, a1, 2));
          m0 = __int_as_float(a0); m1 = __int_as_float(a1);
          th0 = __float_as_int(m0 + TAU_RAW); th1 = __float_as_int(m1 + TAU_RAW);
          l0 = 0.f; l1 = 0.f;
          refresh = __any_sync(0xffffffffu, (a0 | a1) < 0);
        } else {
          refresh = __any_sync(0xffffffffu, (a0 >= th0) || (a1 >= th1));
        }
      }
      if (refresh) {
        float x0 = fmaxf(s[0], s[1]), x1 = fmaxf(s[2], s[3]), y0 = fmaxf(s[4], s[5]), y1 = fmaxf(s[6], s[7]);
        #pragma unroll
        for (int i = 2; i < 16; i += 2) {
          x0 = fmaxf(x0, fmaxf(s[4 * i], s[4 * i + 1]));
          x1 = fmaxf(x1, fmaxf(s[4 * i + 2], s[4 * i + 3]));
          y0 = fmaxf(y0, fmaxf(s[4 * i + 4], s[4 * i + 5]));
          y1 = fmaxf(y1, fmaxf(s[4 * i + 6], s[4 * i + 7]));
        }
        x0 = fmaxf(x0, y0); x1 = fmaxf(x1, y1);
        x0 = fmaxf(x0, __shfl_xor_sync(0xffffffffu, x0, 1));
        x1 = fmaxf(x1, __shfl_xor_sync(0xffffffffu, x1, 1));
        x0 = fmaxf(x0, __shfl_xor_sync(0xffffffffu, x0, 2));
        x1 = fmaxf(x1, __shfl_xor_sync(0xffffffffu, x1, 2));
        if (!FIRST) {
          x0 = fmaxf(x0, m0); x1 = fmaxf(x1, m1);
          const float a0 = ex2((m0 - x0) * cs), a1 = ex2((m1 - x1) * cs);
          l0 *= a0; l1 *= a1;
          #pragma unroll
          for (int i = 0; i < 32; i++) {
            o[4 * i] *= a0; o[4 * i + 1] *= a0; o[4 * i + 2] *= a1; o[4 * i + 3] *= a1;
          }
        }
        m0 = x0; m1 = x1;
        const float t0 = x0 + TAU_RAW, t1 = x1 + TAU_RAW;
        th0 = t0 > 0.f ? __float_as_int(t0) : (int)0x80000000;
        th1 = t1 > 0.f ? __float_as_int(t1) : (int)0x80000000;
      }
      const float mc0 = -m0 * cs, mc1 = -m1 * cs;

      #pragma unroll
      for (int c = 0; c < 4; c++) {
        #pragma unroll
        for (int i = 4 * c; i < 4 * c + 4; i++) {
          const float e0 = ex2(fmaf(s[4 * i], cs, mc0)), e1 = ex2(fmaf(s[4 * i + 1], cs, mc0));
          const float e2 = ex2(fmaf(s[4 * i + 2], cs, mc1)), e3 = ex2(fmaf(s[4 * i + 3], cs, mc1));
          vadd(l0, e0); vadd(l1, e2); vadd(l0, e1); vadd(l1, e3);
          p[2 * i] = pack_bf16(e0, e1);
          p[2 * i + 1] = pack_bf16(e2, e3);
        }
        constexpr int C0 = 1;
        if (c < C0) continue;
        if (c == C0) {
          if (FIRST) {
            pack_half1(ob);
            if (t > 0 && w == 1) flush_half(0);
            #pragma unroll
            for (int i = 0; i < 128; i++) asm volatile("" : "=f"(o[i]));
          }
          rdy = mbar_test4(sBar + BAR_VF + (p[8 * C0 + 7] & zero), kvph);
          bar_sync(1 + w + (rdy & zero), 256);
        }
        #pragma unroll
        for (int cc = (c == C0 ? 0 : c); cc <= c; cc++) {
          if (!(rdy & (1 << cc))) mbar_wait(sBar + BAR_VF + 8 * cc, kvph);
          wg_fence();
          if (FIRST && cc == 0) wgmma_pv<0>(o, p[0], p[1], p[2], p[3], DESC_V);
          else wgmma_pv<1>(o, p[8 * cc], p[8 * cc + 1], p[8 * cc + 2], p[8 * cc + 3], DESC_V + ((cc * 16384) >> 4));
          wgmma_pv<1>(o, p[8 * cc + 4], p[8 * cc + 5], p[8 * cc + 6], p[8 * cc + 7], DESC_V + ((cc * 16384 + 2048) >> 4));
          wg_commit();
        }
      }
      bar_arrive(2 - w, 256);
      if (armer) {
        #pragma unroll
        for (int c = 0; c < 4; c++) mbar_expect(sBar + BAR_VF + 8 * c, 16384);
      }
      if (!FIRST && j == 3) {
        l0 += __shfl_xor_sync(0xffffffffu, l0, 1);
        l1 += __shfl_xor_sync(0xffffffffu, l1, 1);
        l0 += __shfl_xor_sync(0xffffffffu, l0, 2);
        l1 += __shfl_xor_sync(0xffffffffu, l1, 2);
        l0 = rcp(l0); l1 = rcp(l1);
        orow_prev = qrow + w * 64 + wi * 16;
        qrow = qrow_of(t + 1);
        staging_free();
      }
      wg_wait<3>(); if (tid_in_wg == 0) mbar_arrive_cluster(remBar + BAR_VE);
      wg_wait<2>(); if (tid_in_wg == 32) mbar_arrive_cluster(remBar + BAR_VE);
      if (FIRST && t > 0) { staging_free(); stage_half(ob, 0); }
      wg_wait<1>(); if (tid_in_wg == 64) mbar_arrive_cluster(remBar + BAR_VE);
      wg_wait<0>(); if (tid_in_wg == 96) mbar_arrive_cluster(remBar + BAR_VE);
      kvph ^= 1;
    };

    #pragma unroll
    for (int i = 0; i < 128; i++) o[i] = 0.f;
    #pragma unroll
    for (int i = 0; i < 32; i++) oa[i] = 0;
    for (int t = 0; qrow >= 0; t++) {
      block(TrueT{}, t, 0);
      #pragma unroll 1
      for (int j = 1; j < 4; j++) block(FalseT{}, t, j);
      qph ^= 1;
      rdy0 = mbar_test4(sBar + BAR_KF, kvph) & mbar_test4(sBar + BAR_QF + 32 * w, qph);
      #pragma unroll
      for (int i = 0; i < 32; i++) oa[i] = pack_bf16(o[4 * i] * l0, o[4 * i + 1] * l0);
      if (w == 0 || qrow < 0) stage_half(oa, 0);
      #pragma unroll
      for (int i = 0; i < 32; i++) { vmul(o[4 * i + 2], l1); vmul(o[4 * i + 3], l1); }
    }
    {
      const uint32_t off2 = (OFF_Q + w * 32768 + wi * 4096) - (OFF_O + (w * 4 + wi) * 4096);
      uint32_t ob[32];
      pack_half1(ob);
      stage_half(ob, off2);
      asm volatile("fence.proxy.async.shared::cta;" ::: "memory");
      __syncwarp();
      if (lane == 0) {
        tma_store_3d(&tm.o, sO, orow_prev);
        tma_store_3d(&tm.o, sO + off2, orow_prev + 8);
        asm volatile("cp.async.bulk.commit_group;" ::: "memory");
      }
    }
    if (w == 0) bar_sync(1, 256);
    if (lane == 0) asm volatile("cp.async.bulk.wait_group.read 0;" ::: "memory");
    __syncwarp();
    cluster_arrive();
    cluster_wait();
  }
}

typedef CUresult (*EncodeFn)(CUtensorMap*, CUtensorMapDataType, cuuint32_t, void*, const cuuint64_t*, const cuuint64_t*,
                             const cuuint32_t*, const cuuint32_t*, CUtensorMapInterleave, CUtensorMapSwizzle,
                             CUtensorMapL2promotion, CUtensorMapFloatOOBfill);

void make_map(EncodeFn enc, CUtensorMap* tm, void* ptr, uint32_t rows, uint32_t chunks) {
  cuuint64_t dims[3] = {64, (cuuint64_t)NHEADS * SEQ, 4};
  cuuint64_t strides[2] = {HD * 2, 128};
  cuuint32_t box[3] = {64, rows, chunks};
  cuuint32_t es[3] = {1, 1, 1};
  enc(tm, CU_TENSOR_MAP_DATA_TYPE_BFLOAT16, 3, ptr, dims, strides, box, es, CU_TENSOR_MAP_INTERLEAVE_NONE,
      CU_TENSOR_MAP_SWIZZLE_128B, CU_TENSOR_MAP_L2_PROMOTION_L2_128B, CU_TENSOR_MAP_FLOAT_OOB_FILL_NONE);
}
void make_pf_map(EncodeFn enc, CUtensorMap* tm, void* ptr) {
  cuuint64_t dims[2] = {64, (cuuint64_t)NHEADS * SEQ * 4};
  cuuint64_t strides[1] = {128};
  cuuint32_t box[2] = {8, 128};
  cuuint32_t es[2] = {1, 1};
  enc(tm, CU_TENSOR_MAP_DATA_TYPE_BFLOAT16, 2, ptr, dims, strides, box, es, CU_TENSOR_MAP_INTERLEAVE_NONE,
      CU_TENSOR_MAP_SWIZZLE_NONE, CU_TENSOR_MAP_L2_PROMOTION_L2_128B, CU_TENSOR_MAP_FLOAT_OOB_FILL_NONE);
}

}

extern "C" void kernel_launch(void* const* d_in, const int* in_sizes, int n_in, void* d_out, int out_size) {
  static EncodeFn enc = nullptr;
  static int nA = 0, nB = 0;
  cudaLaunchConfig_t cfg = {};
  cfg.blockDim = dim3(NTHREADS); cfg.dynamicSmemBytes = SMEM_BYTES; cfg.stream = cudaStreamPerThread;
  cudaLaunchAttribute at[2];
  at[0].id = cudaLaunchAttributeClusterDimension;
  at[0].val.clusterDim.x = 4; at[0].val.clusterDim.y = 1; at[0].val.clusterDim.z = 1;
  at[1].id = cudaLaunchAttributeProgrammaticStreamSerialization;
  at[1].val.programmaticStreamSerializationAllowed = 1;
  cfg.attrs = at; cfg.numAttrs = 1;
  if (!enc) {
    void* fn = nullptr;
    cudaDriverEntryPointQueryResult st;
    cudaGetDriverEntryPoint("cuTensorMapEncodeTiled", &fn, cudaEnableDefault, &st);
    enc = (EncodeFn)fn;
    cudaFuncSetAttribute(mha_fwd_kernel<2>, cudaFuncAttributeMaxDynamicSharedMemorySize, SMEM_BYTES);
    cudaFuncSetAttribute(mha_fwd_kernel<4>, cudaFuncAttributeMaxDynamicSharedMemorySize, SMEM_BYTES);
    int dev = 0, sms = 0;
    cudaGetDevice(&dev);
    cudaDeviceGetAttribute(&sms, cudaDevAttrMultiProcessorCount, dev);
    cfg.gridDim = dim3(sms & ~3);
    if (cudaOccupancyMaxActiveClusters(&nA, mha_fwd_kernel<4>, &cfg) != cudaSuccess) { (void)cudaGetLastError(); nA = 0; }
    if (nA > sms / 4) nA = sms / 4;
    if (nA > NHEADS / 2) nA = NHEADS / 2;
    nB = (sms - 4 * nA) / 2;
    if (nB > NHEADS) nB = NHEADS;
  }
  Maps tm;
  make_map(enc, &tm.q, d_in[0], 64, 1);
  make_map(enc, &tm.k, d_in[1], 128, 1);
  make_map(enc, &tm.v, d_in[2], 32, 4);
  make_map(enc, &tm.o, d_out, 8, 4);
  make_pf_map(enc, &tm.pq, d_in[0]);
  make_pf_map(enc, &tm.pk, d_in[1]);
  make_pf_map(enc, &tm.pv, d_in[2]);

  int R = 1;
  while (nA * R + (nB * R) / 2 < NHEADS) R++;
  const int hB = NHEADS - nA * R > 0 ? NHEADS - nA * R : 0;
  const int hA = NHEADS - hB;
  if (nA > 0) {
    cfg.gridDim = dim3(4 * nA);
    cudaLaunchKernelEx(&cfg, mha_fwd_kernel<4>, tm, 0, hA / nA, hA % nA, nA);
    cfg.numAttrs = 2;
  }
  if (hB > 0) {
    const int nb = nB < 2 * hB ? nB : 2 * hB;
    at[0].val.clusterDim.x = 2;
    cfg.gridDim = dim3(2 * nb);
    cudaLaunchKernelEx(&cfg, mha_fwd_kernel<2>, tm, 2 * hA, 2 * hB / nb, 2 * hB % nb, nb);
  }
}
```
